```python
import torch

def _softmax(x, axis=-1):
    return torch.softmax(x, dim=axis)

def _gelu(x):
    return torch.nn.functional.gelu(x, approximate='tanh')

def _silu(x):
    return torch.nn.functional.silu(x)

def _sigmoid(x):
    return torch.sigmoid(x)

def _layernorm(x, axis=-1, eps=1e-05):
    m = x.mean(dim=axis, keepdim=True)
    v = x.var(dim=axis, keepdim=True, unbiased=False)
    return (x - m) / torch.sqrt(v + eps)

def _scatter_add(tgt, idx, src, axis=0):
    return tgt.clone().index_add_(axis, idx, src)

def _segment_sum(src, seg, n):
    out = torch.zeros((n,) + src.shape[1:], dtype=src.dtype)
    return out.index_add_(0, seg, src)

def _pad(x, pw):
    flat = tuple((v for pair in reversed(pw) for v in pair))
    return torch.nn.functional.pad(x, flat)
kernel_name = 'standalone__tree_speculative_verify_tree_attention_over_candidate_token_tree__sampling'

def setup_inputs():

    _w = lambda a: (lambda t: t.to(torch.bfloat16) if t.is_floating_point() else t)(torch.as_tensor(a))
    B, Hq, Hkv, T, C, D = (16, 32, 32, 4, 2048, 128)
    tree_mask = torch.zeros((B, T, T), dtype=float)
    for b in range(B):
        parent = torch.zeros(T, dtype=torch.int64)
        for i in range(1, T):
            parent[i] = int(torch.randint(0, i, (1,)).item())
        for i in range(T):
            j = i
            tree_mask[b, i, j] = 1.0
            while j > 0:
                j = parent[j]
                tree_mask[b, i, j] = 1.0
    return {'q': _w((lambda *s: torch.randn(*s, dtype=torch.bfloat16) * 0.8)(B, Hq, T, D)), 'k_cache': _w((lambda *s: torch.randn(*s, dtype=torch.bfloat16) * 0.8)(B, Hkv, C, D)), 'v_cache': _w((lambda *s: torch.randn(*s, dtype=torch.bfloat16) * 0.05)(B, Hkv, C, D)), 'k_tree': _w((lambda *s: torch.randn(*s, dtype=torch.bfloat16) * 0.8)(B, Hkv, T, D)), 'v_tree': _w((lambda *s: torch.randn(*s, dtype=torch.bfloat16) * 0.05)(B, Hkv, T, D)), 'tree_mask': _w(tree_mask)}

def reference(q, k_cache, v_cache, k_tree, v_tree, tree_mask):
    B, Hq, T, D = q.shape
    Hkv, C = (k_cache.shape[1], k_cache.shape[2])
    rep = Hq // Hkv
    kc = (lambda x, n, axis: torch.repeat_interleave(x, n, dim=axis))(k_cache, rep, axis=1)
    vc = (lambda x, n, axis: torch.repeat_interleave(x, n, dim=axis))(v_cache, rep, axis=1)
    kt = (lambda x, n, axis: torch.repeat_interleave(x, n, dim=axis))(k_tree, rep, axis=1)
    vt = (lambda x, n, axis: torch.repeat_interleave(x, n, dim=axis))(v_tree, rep, axis=1)
    k = torch.concatenate([kc, kt], axis=2)
    v = torch.concatenate([vc, vt], axis=2)
    scale = D ** (-0.5)
    scores = torch.einsum('bhqd,bhkd->bhqk', q, k) * scale
    ctx_mask = torch.ones((B, 1, T, C), dtype=scores.dtype)
    tm = tree_mask[:, None, :, :].clone()
    full_mask = torch.concatenate([ctx_mask, tm], axis=-1)
    scores = scores + (1.0 - full_mask) * -1000000000.0
    p = _softmax(scores, axis=-1)
    return torch.einsum('bhqk,bhkd->bhqd', p, v)
```

```cpp
#include <cuda_runtime.h>
#include <cuda_bf16.h>
#include <cuda.h>
#include <stdint.h>

namespace {

constexpr int kBatch = 16, kHeads = 32, kT = 4, kCtx = 2048, kD = 128;
constexpr int kNumHeads = kBatch * kHeads;
constexpr int kTile = 64;
constexpr int kTilesPerHead = kCtx / kTile;
constexpr int kSlotBytes = kTile * kD * 2;
constexpr int kQBytes = kT * kD * 2;
constexpr int kMaxLev = 6;
constexpr int kMaxSlots = 12;
constexpr int kOStride = 136;
constexpr int kPartFloats = 520;
constexpr int kThreads = 192;

constexpr uint32_t KIND_WHOLE = 0, KIND_PARK = 1, KIND_FINAL = 2, KIND_PART = 3;
constexpr uint32_t META_FIRST = 1u << 9, META_LAST = 1u << 10;

struct Params {
    const __nv_bfloat16* q;
    const __nv_bfloat16* kt;
    const __nv_bfloat16* vt;
    const __nv_bfloat16* mask;
    __nv_bfloat16* out;
    int nslots;
    int depth;
    int xb;
    int nw;
    int ns;
    int nlev;
    int npool;
    int look;
    int hint;
    int pf;
    int lvl_start[kMaxLev];
    int lvl_len[kMaxLev];
};

__device__ unsigned int g_queue;
__device__ float g_part[kNumHeads * kMaxLev * kPartFloats];
#define TICK(i)

__device__ __forceinline__ uint32_t smem_u32(const void* p) { return (uint32_t)__cvta_generic_to_shared(p); }
__device__ __forceinline__ void mbar_init(uint32_t bar, uint32_t cnt) {
    asm volatile("mbarrier.init.shared::cta.b64 [%0], %1;" ::"r"(bar), "r"(cnt) : "memory");
}
__device__ __forceinline__ void mbar_arrive(uint32_t bar) {
    asm volatile("mbarrier.arrive.shared::cta.b64 _, [%0];" ::"r"(bar) : "memory");
}
__device__ __forceinline__ void mbar_expect_tx(uint32_t bar, uint32_t bytes) {
    asm volatile("mbarrier.arrive.expect_tx.shared::cta.b64 _, [%0], %1;" ::"r"(bar), "r"(bytes) : "memory");
}
__device__ __forceinline__ bool mbar_try(uint32_t bar, uint32_t parity) {
    uint32_t ok;
    asm volatile(
        "{\n.reg .pred p;\n"
        "mbarrier.try_wait.parity.shared::cta.b64 p, [%1], %2;\n"
        "selp.u32 %0, 1, 0, p;\n}"
        : "=r"(ok) : "r"(bar), "r"(parity) : "memory");
    return ok != 0;
}
__device__ __forceinline__ void mbar_wait(uint32_t bar, uint32_t parity) {
    if (mbar_try(bar, parity)) return;
    const long long t0 = clock64();
    while (!mbar_try(bar, parity)) {
        if (clock64() - t0 > 4000000000LL) __trap();
    }
}
__device__ __forceinline__ void tma_tile(uint32_t dst, const CUtensorMap* map, int row, uint32_t bar, int hint, uint64_t pol) {
    if (hint)
        asm volatile("cp.async.bulk.tensor.3d.shared::cluster.global.mbarrier::complete_tx::bytes.L2::cache_hint"
                     " [%0], [%1, {%3, %4, %3}], [%2], %5;"
                     ::"r"(dst), "l"(map), "r"(bar), "r"(0), "r"(row), "l"(pol) : "memory");
    else
        asm volatile("cp.async.bulk.tensor.3d.shared::cluster.global.mbarrier::complete_tx::bytes"
                     " [%0], [%1, {%3, %4, %3}], [%2];"
                     ::"r"(dst), "l"(map), "r"(bar), "r"(0), "r"(row) : "memory");
}
__device__ __forceinline__ void bulk_copy(uint32_t dst, const void* src, uint32_t bytes, uint32_t bar) {
    asm volatile("cp.async.bulk.shared::cluster.global.mbarrier::complete_tx::bytes [%0], [%1], %2, [%3];"
                 ::"r"(dst), "l"(src), "r"(bytes), "r"(bar) : "memory");
}
__device__ __forceinline__ void ldsm4(uint32_t addr, uint32_t (&r)[4]) {
    asm volatile("ldmatrix.sync.aligned.m8n8.x4.shared.b16 {%0,%1,%2,%3}, [%4];"
                 : "=r"(r[0]), "=r"(r[1]), "=r"(r[2]), "=r"(r[3]) : "r"(addr) : "memory");
}
__device__ __forceinline__ void ldsm4_t(uint32_t addr, uint32_t (&r)[4]) {
    asm volatile("ldmatrix.sync.aligned.m8n8.x4.trans.shared.b16 {%0,%1,%2,%3}, [%4];"
                 : "=r"(r[0]), "=r"(r[1]), "=r"(r[2]), "=r"(r[3]) : "r"(addr) : "memory");
}
__device__ __forceinline__ void mma_bf16(float (&c)[4], const uint32_t (&a)[4], uint32_t b0, uint32_t b1) {
    asm volatile("mma.sync.aligned.m16n8k16.row.col.f32.bf16.bf16.f32 {%0,%1,%2,%3}, {%4,%5,%6,%7}, {%8,%9}, {%0,%1,%2,%3};"
                 : "+f"(c[0]), "+f"(c[1]), "+f"(c[2]), "+f"(c[3])
                 : "r"(a[0]), "r"(a[1]), "r"(a[2]), "r"(a[3]), "r"(b0), "r"(b1));
}
__device__ __forceinline__ uint32_t pack_bf16(float lo, float hi) {
    uint32_t r;
    asm("cvt.rn.bf16x2.f32 %0, %1, %2;" : "=r"(r) : "f"(hi), "f"(lo));
    return r;
}
__device__ __forceinline__ uint32_t movmatrix_t(uint32_t a) {
    uint32_t d;
    asm volatile("movmatrix.sync.aligned.m8n8.trans.b16 %0, %1;" : "=r"(d) : "r"(a));
    return d;
}
__device__ __forceinline__ float ex2(float x) {
    float y;
    asm("ex2.approx.ftz.f32 %0, %1;" : "=f"(y) : "f"(x));
    return y;
}
__device__ __forceinline__ float bf_lo(uint32_t v) { return __uint_as_float(v << 16); }
__device__ __forceinline__ float bf_hi(uint32_t v) { return __uint_as_float(v & 0xffff0000u); }
__device__ __forceinline__ float lds_f32(uint32_t a) {
    float v;
    asm volatile("ld.shared.f32 %0, [%1];" : "=f"(v) : "r"(a) : "memory");
    return v;
}
__device__ __forceinline__ uint32_t lds_u32(uint32_t a) {
    uint32_t v;
    asm volatile("ld.shared.u32 %0, [%1];" : "=r"(v) : "r"(a) : "memory");
    return v;
}
__device__ __forceinline__ float4 lds_f32x4(uint32_t a) {
    float4 v;
    asm volatile("ld.shared.v4.f32 {%0,%1,%2,%3}, [%4];" : "=f"(v.x), "=f"(v.y), "=f"(v.z), "=f"(v.w) : "r"(a) : "memory");
    return v;
}
__device__ __forceinline__ void sts_f32(uint32_t a, float v) { asm volatile("st.shared.f32 [%0], %1;" ::"r"(a), "f"(v) : "memory"); }
__device__ __forceinline__ void sts_u32(uint32_t a, uint32_t v) { asm volatile("st.shared.u32 [%0], %1;" ::"r"(a), "r"(v) : "memory"); }

__device__ __forceinline__ uint32_t enc_word(float x) { return max(__float_as_uint(x), 1u); }
__device__ __forceinline__ void st_part(float* p, float a, float b, float c, float d) {
    asm volatile("st.relaxed.gpu.global.v4.b32 [%0], {%1,%2,%3,%4};"
                 ::"l"(p), "r"(enc_word(a)), "r"(enc_word(b)), "r"(enc_word(c)), "r"(enc_word(d)) : "memory");
}
__device__ __forceinline__ void clear_part(float* p) {
    asm volatile("st.relaxed.gpu.global.v4.b32 [%0], {%1,%1,%1,%1};" ::"l"(p), "r"(0u) : "memory");
}
__device__ __forceinline__ void ld_part(const float* p, uint4& v, bool pred) {
    asm volatile("{\n.reg .pred p;\nsetp.ne.u32 p, %5, 0;\n@p ld.relaxed.gpu.global.v4.b32 {%0,%1,%2,%3}, [%4];\n}"
                 : "+r"(v.x), "+r"(v.y), "+r"(v.z), "+r"(v.w) : "l"(p), "r"((uint32_t)pred) : "memory");
}
__device__ __forceinline__ bool all_set(const uint4& v) { return v.x != 0 && v.y != 0 && v.z != 0 && v.w != 0; }
__device__ __forceinline__ float comp(const uint4& v, int i) {
    return __uint_as_float(i == 0 ? v.x : i == 1 ? v.y : i == 2 ? v.z : v.w);
}
__device__ __forceinline__ void prefetch_l2(const void* src, uint32_t bytes) {
    asm volatile("cp.async.bulk.prefetch.L2.global [%0], %1;" ::"l"(src), "r"(bytes) : "memory");
}

constexpr float kLog2e = 1.4426950408889634f;
constexpr float kScale = 0.08838834764831845f;
constexpr float kScaleLog2e = kScale * kLog2e;

struct RowState {
    float o[kT][4];
    float m[kT];
    float l[kT];
};

__device__ __forceinline__ void tree_part(const Params& p, int head, int lane, RowState& r) {
    const size_t base = (size_t)head * (kT * kD) + 4 * lane;
    uint2 qv[kT], kv[kT], vv[kT];
#pragma unroll
    for (int i = 0; i < kT; i++) {
        qv[i] = __ldg(reinterpret_cast<const uint2*>(p.q + base + i * kD));
        kv[i] = __ldg(reinterpret_cast<const uint2*>(p.kt + base + i * kD));
        vv[i] = __ldg(reinterpret_cast<const uint2*>(p.vt + base + i * kD));
    }
    const uint4* mp = reinterpret_cast<const uint4*>(p.mask + (size_t)(head / kHeads) * (kT * kT));
    const uint4 mk0 = __ldg(mp), mk1 = __ldg(mp + 1);
    const uint32_t mw[8] = {mk0.x, mk0.y, mk0.z, mk0.w, mk1.x, mk1.y, mk1.z, mk1.w};
    float s[kT][kT];
#pragma unroll
    for (int i = 0; i < kT; i++)
#pragma unroll
        for (int j = 0; j < kT; j++) {
            float a = bf_lo(qv[i].x) * bf_lo(kv[j].x);
            a = fmaf(bf_hi(qv[i].x), bf_hi(kv[j].x), a);
            a = fmaf(bf_lo(qv[i].y), bf_lo(kv[j].y), a);
            a = fmaf(bf_hi(qv[i].y), bf_hi(kv[j].y), a);
            s[i][j] = a;
        }
#pragma unroll
    for (int off = 16; off > 0; off >>= 1)
#pragma unroll
        for (int i = 0; i < kT; i++)
#pragma unroll
            for (int j = 0; j < kT; j++) s[i][j] += __shfl_xor_sync(0xffffffffu, s[i][j], off);
#pragma unroll
    for (int i = 0; i < kT; i++) {
        float t[kT];
        float m = -INFINITY;
#pragma unroll
        for (int j = 0; j < kT; j++) {
            const uint32_t w = mw[i * 2 + (j >> 1)];
            const float mk = (j & 1) ? bf_hi(w) : bf_lo(w);
            t[j] = (s[i][j] * kScale + (1.0f - mk) * -1000000000.0f) * kLog2e;
            m = fmaxf(m, t[j]);
        }
        float l = 0.f, o0 = 0.f, o1 = 0.f, o2 = 0.f, o3 = 0.f;
#pragma unroll
        for (int j = 0; j < kT; j++) {
            const float pj = ex2(t[j] - m);
            l += pj;
            o0 = fmaf(pj, bf_lo(vv[j].x), o0);
            o1 = fmaf(pj, bf_hi(vv[j].x), o1);
            o2 = fmaf(pj, bf_lo(vv[j].y), o2);
            o3 = fmaf(pj, bf_hi(vv[j].y), o3);
        }
        r.m[i] = m; r.l[i] = l;
        r.o[i][0] = o0; r.o[i][1] = o1; r.o[i][2] = o2; r.o[i][3] = o3;
    }
}

__device__ __forceinline__ void merge_state(RowState& a, const RowState& b) {
#pragma unroll
    for (int i = 0; i < kT; i++) {
        const float m = fmaxf(a.m[i], b.m[i]);
        const float wa = ex2(a.m[i] - m), wb = ex2(b.m[i] - m);
        a.m[i] = m;
        a.l[i] = a.l[i] * wa + b.l[i] * wb;
#pragma unroll
        for (int e = 0; e < 4; e++) a.o[i][e] = a.o[i][e] * wa + b.o[i][e] * wb;
    }
}

__device__ __forceinline__ void write_out(const Params& p, int head, int lane, const RowState& r) {
#pragma unroll
    for (int i = 0; i < kT; i++) {
        const float inv = __frcp_rn(r.l[i]);
        uint2 v;
        v.x = pack_bf16(r.o[i][0] * inv, r.o[i][1] * inv);
        v.y = pack_bf16(r.o[i][2] * inv, r.o[i][3] * inv);
        *reinterpret_cast<uint2*>(p.out + (size_t)head * (kT * kD) + i * kD + 4 * lane) = v;
    }
}

__global__ void __launch_bounds__(kThreads, 1)
tree_attn_kernel(const __grid_constant__ Params p, const __grid_constant__ CUtensorMap map_k,
                 const __grid_constant__ CUtensorMap map_v) {
    extern __shared__ __align__(1024) uint8_t smem_raw[];
    const uint32_t smem_base = (smem_u32(smem_raw) + 1023u) & ~1023u;
    const int nslots = p.nslots;
    const uint32_t s_tile = smem_base;
    const uint32_t s_q = s_tile + nslots * kSlotBytes;
    const uint32_t s_o = s_q + nslots * kQBytes;
    const uint32_t s_ml = s_o + 2 * 4 * kT * kOStride * 4;
    const uint32_t s_meta = s_ml + 2 * 4 * 8 * 4;
    const uint32_t s_cmeta = s_meta + kMaxSlots * 4;
    const uint32_t s_full = s_cmeta + 16;
    const uint32_t s_empty = s_full + kMaxSlots * 8;
    const uint32_t s_cfull = s_empty + kMaxSlots * 8;
    const uint32_t s_cempty = s_cfull + 16;

    const int warp = threadIdx.x >> 5;
    const int lane = threadIdx.x & 31;

    if (warp == 4) {
        if (lane == 0) {
            asm volatile("prefetch.tensormap [%0];" ::"l"(&map_k) : "memory");
            asm volatile("prefetch.tensormap [%0];" ::"l"(&map_v) : "memory");
            for (int i = 0; i < nslots; i++) {
                mbar_init(s_full + i * 8, 1);
                mbar_init(s_empty + i * 8, 4);
            }
            mbar_init(s_cfull, 4); mbar_init(s_cfull + 8, 4);
            mbar_init(s_cempty, 1); mbar_init(s_cempty + 8, 1);
            asm volatile("fence.mbarrier_init.release.cluster;" ::: "memory");
            asm volatile("fence.proxy.async.shared::cta;" ::: "memory");
        }
        __syncwarp();
        asm volatile("bar.arrive 1, %0;" ::"n"(kThreads) : "memory");
        if (lane == 0) {
            uint64_t pol = 0;
            if (p.hint) asm volatile("createpolicy.fractional.L2::evict_first.b64 %0, 1.0;" : "=l"(pol));
            const unsigned wrap = (unsigned)(p.npool + gridDim.x - 1);
            uint32_t slot = 0, phase = 1;
            uint32_t wslot = 0, wphase = 0;
            int lag = -p.depth;
            int head = blockIdx.x, t0 = 0, n = kTilesPerHead - p.xb;
            uint32_t tag = KIND_PARK << 11;
            while (true) {
                const bool is_final = (tag >> 11 & 3u) == KIND_FINAL;
                const int fetch_at = n > p.look ? n - p.look : 0;
                unsigned nxt = 0;
                const int row0 = head * kCtx + t0 * kTile;
                for (int j = 0; j < n; j++) {
                    if (j == fetch_at && !is_final) nxt = atomicInc(&g_queue, wrap);
                    if (lag >= 0) {
                        if (!is_final) mbar_wait(s_empty + wslot * 8, wphase);
                        if (++wslot == (uint32_t)nslots) { wslot = 0; wphase ^= 1; }
                    }
                    lag++;
                    mbar_wait(s_empty + slot * 8, phase);
                    uint32_t meta = tag | (uint32_t)head;
                    if (j == 0) meta |= META_FIRST;
                    if (j == n - 1) meta |= META_LAST;
                    sts_u32(s_meta + slot * 4, meta);
                    mbar_expect_tx(s_full + slot * 8, j == 0 ? kSlotBytes + kQBytes : kSlotBytes);
                    tma_tile(s_tile + slot * kSlotBytes, &map_k, row0 + j * kTile, s_full + slot * 8, p.hint, pol);
                    if (j == 0) {
                        bulk_copy(s_q + slot * kQBytes, p.q + (size_t)head * (kT * kD), kQBytes, s_full + slot * 8);
                        if (t0 == 0 && p.pf) {
                            prefetch_l2(p.kt + (size_t)head * (kT * kD), kQBytes);
                            prefetch_l2(p.vt + (size_t)head * (kT * kD), kQBytes);
                        }
                    }
                    if (++slot == (uint32_t)nslots) { slot = 0; phase ^= 1; }
                    if (lag >= 0) {
                        if (!is_final) mbar_wait(s_empty + wslot * 8, wphase);
                        if (++wslot == (uint32_t)nslots) { wslot = 0; wphase ^= 1; }
                    }
                    lag++;
                    mbar_wait(s_empty + slot * 8, phase);
                    mbar_expect_tx(s_full + slot * 8, kSlotBytes);
                    tma_tile(s_tile + slot * kSlotBytes, &map_v, row0 + j * kTile, s_full + slot * 8, p.hint, pol);
                    if (++slot == (uint32_t)nslots) { slot = 0; phase ^= 1; }
                }
                if (is_final) break;
                if (nxt < (unsigned)p.nw) {
                    head = gridDim.x + nxt; t0 = 0; n = kTilesPerHead; tag = KIND_WHOLE << 11;
                } else if (nxt < (unsigned)p.npool) {
                    const int r = nxt - p.nw;
                    const int lev = r / p.ns;
                    head = gridDim.x + p.nw + (r - lev * p.ns);
                    t0 = p.lvl_start[lev]; n = p.lvl_len[lev];
                    tag = (KIND_PART << 11) | ((uint32_t)lev << 13);
                } else {
                    head = blockIdx.x; t0 = kTilesPerHead - p.xb; n = p.xb; tag = KIND_FINAL << 11;
                }
            }
        }
    } else if (warp < 4) {
        const int g = lane >> 2, t = lane & 3;
        uint32_t koff[4], voff[4];
        {
            const uint32_t krow = 16 * warp + (lane & 7) + 8 * ((lane >> 3) & 1);
            const uint32_t kx = (lane >> 4) ^ (lane & 7);
            const uint32_t vrow = 16 * warp + (lane & 7) + 8 * (lane >> 4);
            const uint32_t vx = ((lane >> 3) & 1) ^ (lane & 7);
#pragma unroll
            for (int i = 0; i < 4; i++) {
                koff[i] = s_tile + krow * 128 + (((2 * i) ^ kx) << 4);
                voff[i] = s_tile + vrow * 128 + (((2 * i) ^ vx) << 4);
            }
        }
        float o[8][4], po[8][4];
        float m0 = 0.f, m1 = 0.f, l0 = 0.f, l1 = 0.f, pm0 = 0.f, pm1 = 0.f, pl0 = 0.f, pl1 = 0.f;
        uint32_t qf[8][2];
#pragma unroll
        for (int i = 0; i < 8; i++) {
            qf[i][0] = qf[i][1] = 0;
#pragma unroll
            for (int e = 0; e < 4; e++) { o[i][e] = 0.f; po[i][e] = 0.f; }
        }
        uint32_t slot = 0, phase = 0, cbuf = 0, cphase = 1;
        asm volatile("bar.sync 1, %0;" ::"n"(kThreads) : "memory");
        while (true) {
            mbar_wait(s_full + slot * 8, phase);
            const uint32_t meta = lds_u32(s_meta + slot * 4);
            const uint32_t kind = (meta >> 11) & 3u;
            if (meta & META_FIRST) {
                const uint32_t qa = s_q + slot * kQBytes + (g & 3) * (kD * 2) + t * 4;
#pragma unroll
                for (int ks = 0; ks < 8; ks++) {
                    qf[ks][0] = lds_u32(qa + ks * 32);
                    qf[ks][1] = lds_u32(qa + ks * 32 + 16);
                }
                if (kind == KIND_FINAL) {
                    m0 = pm0; m1 = pm1; l0 = pl0; l1 = pl1;
#pragma unroll
                    for (int i = 0; i < 8; i++)
#pragma unroll
                        for (int e = 0; e < 4; e++) o[i][e] = po[i][e];
                } else {
                    m0 = m1 = -INFINITY; l0 = l1 = 0.f;
#pragma unroll
                    for (int i = 0; i < 8; i++)
#pragma unroll
                        for (int e = 0; e < 4; e++) o[i][e] = 0.f;
                }
            }
            float sa[4] = {0.f, 0.f, 0.f, 0.f}, sb[4] = {0.f, 0.f, 0.f, 0.f};
            {
                const uint32_t kb = slot * kSlotBytes;
#pragma unroll
                for (int ks = 0; ks < 8; ks += 2) {
                    uint32_t a0[4], a1[4];
                    ldsm4(koff[ks & 3] + kb + (ks >> 2) * 8192, a0);
                    ldsm4(koff[(ks + 1) & 3] + kb + (ks >> 2) * 8192, a1);
                    mma_bf16(sa, a0, qf[ks][0], qf[ks][1]);
                    mma_bf16(sb, a1, qf[ks + 1][0], qf[ks + 1][1]);
                }
            }
            __syncwarp();
            if (lane == 0) mbar_arrive(s_empty + slot * 8);
            if (++slot == (uint32_t)nslots) { slot = 0; phase ^= 1; }

            const float s0 = sa[0] + sb[0], s1 = sa[1] + sb[1], s2 = sa[2] + sb[2], s3 = sa[3] + sb[3];
            float x0 = fmaxf(s0, s2), x1 = fmaxf(s1, s3);
#pragma unroll
            for (int off = 4; off < 32; off <<= 1) {
                x0 = fmaxf(x0, __shfl_xor_sync(0xffffffffu, x0, off));
                x1 = fmaxf(x1, __shfl_xor_sync(0xffffffffu, x1, off));
            }
            const float n0 = fmaxf(m0, x0 * kScaleLog2e), n1 = fmaxf(m1, x1 * kScaleLog2e);
            const float al0 = ex2(m0 - n0), al1 = ex2(m1 - n1);
            m0 = n0; m1 = n1;
            const float p0 = ex2(fmaf(s0, kScaleLog2e, -n0)), p1 = ex2(fmaf(s1, kScaleLog2e, -n1));
            const float p2 = ex2(fmaf(s2, kScaleLog2e, -n0)), p3 = ex2(fmaf(s3, kScaleLog2e, -n1));
            l0 = fmaf(l0, al0, p0 + p2);
            l1 = fmaf(l1, al1, p1 + p3);
            const uint32_t b0 = movmatrix_t(pack_bf16(p0, p1));
            const uint32_t b1 = movmatrix_t(pack_bf16(p2, p3));
#pragma unroll
            for (int i = 0; i < 8; i++) {
                o[i][0] *= al0; o[i][1] *= al1; o[i][2] *= al0; o[i][3] *= al1;
            }
            mbar_wait(s_full + slot * 8, phase);
            {
                const uint32_t vb = slot * kSlotBytes;
#pragma unroll
                for (int mt = 0; mt < 8; mt++) {
                    uint32_t a[4];
                    ldsm4_t(voff[mt & 3] + vb + (mt >> 2) * 8192, a);
                    mma_bf16(o[mt], a, b0, b1);
                }
            }
            __syncwarp();
            if (lane == 0) mbar_arrive(s_empty + slot * 8);
            if (++slot == (uint32_t)nslots) { slot = 0; phase ^= 1; }

            if (meta & META_LAST) {
                if (kind == KIND_PARK) {
                    pm0 = m0; pm1 = m1; pl0 = l0; pl1 = l1;
#pragma unroll
                    for (int i = 0; i < 8; i++)
#pragma unroll
                        for (int e = 0; e < 4; e++) po[i][e] = o[i][e];
                } else {
#pragma unroll
                    for (int off = 4; off < 32; off <<= 1) {
                        l0 += __shfl_xor_sync(0xffffffffu, l0, off);
                        l1 += __shfl_xor_sync(0xffffffffu, l1, off);
                    }
                    mbar_wait(s_cempty + cbuf * 8, cphase);
                    const uint32_t ob = s_o + (cbuf * 4 + warp) * (kT * kOStride * 4);
                    const int qq = 2 * (t & 1), hi = t >> 1;
                    const uint32_t oa = ob + (qq * kOStride + g + 8 * hi) * 4;
#pragma unroll
                    for (int mt = 0; mt < 8; mt++) {
                        sts_f32(oa + mt * 64, hi ? o[mt][2] : o[mt][0]);
                        sts_f32(oa + mt * 64 + kOStride * 4, hi ? o[mt][3] : o[mt][1]);
                    }
                    if (lane < 2) {
                        const uint32_t mb = s_ml + (cbuf * 4 + warp) * 32 + lane * 8;
                        sts_f32(mb, m0); sts_f32(mb + 4, m1);
                        sts_f32(mb + 16, l0); sts_f32(mb + 20, l1);
                    }
                    if (threadIdx.x == 0) sts_u32(s_cmeta + cbuf * 4, meta);
                    __syncwarp();
                    if (lane == 0) mbar_arrive(s_cfull + cbuf * 8);
                    cbuf ^= 1;
                    if (cbuf == 0) cphase ^= 1;
                    if (kind == KIND_FINAL) break;
                }
            }
        }
    } else {
        asm volatile("bar.sync 1, %0;" ::"n"(kThreads) : "memory");
        RowState home;
        tree_part(p, blockIdx.x, lane, home);
        uint32_t cbuf = 0, cphase = 0;
        while (true) {
            mbar_wait(s_cfull + cbuf * 8, cphase);
            const uint32_t meta = lds_u32(s_cmeta + cbuf * 4);
            const uint32_t kind = (meta >> 11) & 3u;
            const int head = meta & 511u;
            const int piece = (meta >> 13) & 7u;
            RowState r;
            {
                float4 mw[4], lw[4];
#pragma unroll
                for (int w = 0; w < 4; w++) {
                    mw[w] = lds_f32x4(s_ml + (cbuf * 4 + w) * 32);
                    lw[w] = lds_f32x4(s_ml + (cbuf * 4 + w) * 32 + 16);
                }
#pragma unroll
                for (int i = 0; i < kT; i++) {
                    float mm[4], ll[4];
#pragma unroll
                    for (int w = 0; w < 4; w++) {
                        mm[w] = i == 0 ? mw[w].x : i == 1 ? mw[w].y : i == 2 ? mw[w].z : mw[w].w;
                        ll[w] = i == 0 ? lw[w].x : i == 1 ? lw[w].y : i == 2 ? lw[w].z : lw[w].w;
                    }
                    const float m = fmaxf(fmaxf(mm[0], mm[1]), fmaxf(mm[2], mm[3]));
                    float l = 0.f, a0 = 0.f, a1 = 0.f, a2 = 0.f, a3 = 0.f;
#pragma unroll
                    for (int w = 0; w < 4; w++) {
                        const float sc = ex2(mm[w] - m);
                        const float4 v = lds_f32x4(s_o + ((cbuf * 4 + w) * kT * kOStride + i * kOStride + 4 * lane) * 4);
                        l = fmaf(ll[w], sc, l);
                        a0 = fmaf(v.x, sc, a0); a1 = fmaf(v.y, sc, a1); a2 = fmaf(v.z, sc, a2); a3 = fmaf(v.w, sc, a3);
                    }
                    r.m[i] = m; r.l[i] = l;
                    r.o[i][0] = a0; r.o[i][1] = a1; r.o[i][2] = a2; r.o[i][3] = a3;
                }
            }
            __syncwarp();
            if (lane == 0) mbar_arrive(s_cempty + cbuf * 8);
            cbuf ^= 1;
            if (cbuf == 0) cphase ^= 1;
            TICK(0);

            if (kind == KIND_FINAL) {
                merge_state(r, home);
                write_out(p, head, lane, r);
                break;
            }
            if (kind == KIND_WHOLE || piece == 0) {
                RowState tr;
                tree_part(p, head, lane, tr);
                merge_state(r, tr);
                TICK(1);
            }
            if (kind == KIND_WHOLE) {
                write_out(p, head, lane, r);
                continue;
            }
            float* part = g_part + (size_t)head * (kMaxLev * kPartFloats);
            const int nprev = p.nlev - 1;
            if (piece < nprev) {
                float* dst = part + piece * kPartFloats;
#pragma unroll
                for (int i = 0; i < kT; i++) st_part(dst + i * kD + 4 * lane, r.o[i][0], r.o[i][1], r.o[i][2], r.o[i][3]);
                if (lane == 0) {
                    st_part(dst + 512, r.m[0], r.m[1], r.m[2], r.m[3]);
                    st_part(dst + 516, r.l[0], r.l[1], r.l[2], r.l[3]);
                }
                TICK(3);
                continue;
            }
            uint4 pm[kMaxLev - 1], pl[kMaxLev - 1], pv[kMaxLev - 1][kT];
            for (int tries = 0;; tries++) {
#pragma unroll
                for (int k = 0; k < kMaxLev - 1; k++) {
                    const float* src = part + k * kPartFloats;
                    const bool on = k < nprev;
                    pm[k] = make_uint4(0xff800000u, 0xff800000u, 0xff800000u, 0xff800000u);
                    pl[k] = make_uint4(1u, 1u, 1u, 1u);
                    ld_part(src + 512, pm[k], on);
                    ld_part(src + 516, pl[k], on);
#pragma unroll
                    for (int i = 0; i < kT; i++) {
                        pv[k][i] = make_uint4(1u, 1u, 1u, 1u);
                        ld_part(src + i * kD + 4 * lane, pv[k][i], on);
                    }
                }
                bool ok = true;
#pragma unroll
                for (int k = 0; k < kMaxLev - 1; k++) {
                    ok &= all_set(pm[k]) && all_set(pl[k]);
#pragma unroll
                    for (int i = 0; i < kT; i++) ok &= all_set(pv[k][i]);
                }
                if (__all_sync(0xffffffffu, ok)) break;
                if (tries > 2000000) __trap();
            }
#pragma unroll
            for (int k = 0; k < kMaxLev - 1; k++) {
                if (k < nprev) {
                    float* src = part + k * kPartFloats;
#pragma unroll
                    for (int i = 0; i < kT; i++) clear_part(src + i * kD + 4 * lane);
                    if (lane < 2) clear_part(src + 512 + 4 * lane);
                }
            }
#pragma unroll
            for (int i = 0; i < kT; i++) {
                float mm[kMaxLev - 1], ll[kMaxLev - 1];
#pragma unroll
                for (int k = 0; k < kMaxLev - 1; k++) {
                    mm[k] = comp(pm[k], i);
                    ll[k] = comp(pl[k], i);
                }
                float m = r.m[i];
#pragma unroll
                for (int k = 0; k < kMaxLev - 1; k++) m = fmaxf(m, mm[k]);
                float l = 0.f, a0 = 0.f, a1 = 0.f, a2 = 0.f, a3 = 0.f;
#pragma unroll
                for (int k = 0; k < kMaxLev - 1; k++) {
                    const float sc = ex2(mm[k] - m);
                    l = fmaf(ll[k], sc, l);
                    a0 = fmaf(comp(pv[k][i], 0), sc, a0); a1 = fmaf(comp(pv[k][i], 1), sc, a1);
                    a2 = fmaf(comp(pv[k][i], 2), sc, a2); a3 = fmaf(comp(pv[k][i], 3), sc, a3);
                }
                const float sc = ex2(r.m[i] - m);
                r.m[i] = m;
                r.l[i] = fmaf(r.l[i], sc, l);
                r.o[i][0] = fmaf(r.o[i][0], sc, a0); r.o[i][1] = fmaf(r.o[i][1], sc, a1);
                r.o[i][2] = fmaf(r.o[i][2], sc, a2); r.o[i][3] = fmaf(r.o[i][3], sc, a3);
            }
            write_out(p, head, lane, r);
            TICK(5);
        }
    }
}

typedef CUresult (*EncodeTiledFn)(CUtensorMap*, CUtensorMapDataType, cuuint32_t, void*, const cuuint64_t*,
                                  const cuuint64_t*, const cuuint32_t*, const cuuint32_t*, CUtensorMapInterleave,
                                  CUtensorMapSwizzle, CUtensorMapL2promotion, CUtensorMapFloatOOBfill);

void make_map(EncodeTiledFn enc, CUtensorMap* m, const void* ptr) {
    cuuint64_t dims[3] = {64, (cuuint64_t)kNumHeads * kCtx, 2};
    cuuint64_t strides[2] = {kD * 2, 128};
    cuuint32_t box[3] = {64, (cuuint32_t)kTile, 2};
    cuuint32_t estr[3] = {1, 1, 1};
    enc(m, CU_TENSOR_MAP_DATA_TYPE_BFLOAT16, 3, const_cast<void*>(ptr), dims, strides, box, estr,
        CU_TENSOR_MAP_INTERLEAVE_NONE, CU_TENSOR_MAP_SWIZZLE_128B, CU_TENSOR_MAP_L2_PROMOTION_L2_256B,
        CU_TENSOR_MAP_FLOAT_OOB_FILL_NONE);
}

struct Tuning {
    int nslots = 4;
    int depth = 4;
    int xb = 4;
    int ns = 132;
    int nlev = 5;
    int lens[kMaxLev] = {16, 8, 4, 2, 2, 0};
    int look = 1;
    int hint = 1;
    int pf = 1;
    int grid = 0;
};

}

extern "C" void kernel_launch(void* const* d_in, const int* in_sizes, int n_in, void* d_out, int out_size) {
    (void)in_sizes; (void)n_in; (void)out_size;
    const Tuning tn;
    static EncodeTiledFn enc = nullptr;
    static int num_sms = 0;
    if (!enc) {
        void* fn = nullptr;
        cudaDriverEntryPointQueryResult qr;
        cudaGetDriverEntryPoint("cuTensorMapEncodeTiled", &fn, cudaEnableDefault, &qr);
        enc = (EncodeTiledFn)fn;
        int dev = 0;
        cudaGetDevice(&dev);
        cudaDeviceGetAttribute(&num_sms, cudaDevAttrMultiProcessorCount, dev);
        cudaFuncSetAttribute(tree_attn_kernel, cudaFuncAttributeMaxDynamicSharedMemorySize, 227 * 1024);
    }
    CUtensorMap mk, mv;
    make_map(enc, &mk, d_in[1]);
    make_map(enc, &mv, d_in[2]);

    int grid = tn.grid > 0 ? tn.grid : num_sms;
    if (grid > kNumHeads) grid = kNumHeads;

    Params p;
    p.q = (const __nv_bfloat16*)d_in[0];
    p.kt = (const __nv_bfloat16*)d_in[3];
    p.vt = (const __nv_bfloat16*)d_in[4];
    p.mask = (const __nv_bfloat16*)d_in[5];
    p.out = (__nv_bfloat16*)d_out;
    p.nslots = tn.nslots;
    p.depth = tn.depth < tn.nslots ? tn.depth : tn.nslots;
    p.xb = tn.xb;
    p.ns = tn.ns < kNumHeads - grid ? tn.ns : kNumHeads - grid;
    p.nw = kNumHeads - grid - p.ns;
    p.nlev = tn.nlev;
    p.npool = p.nw + p.ns * p.nlev;
    p.look = tn.look < 1 ? 1 : tn.look;
    p.hint = tn.hint;
    p.pf = tn.pf;
    int start = 0;
    for (int i = 0; i < kMaxLev; i++) {
        p.lvl_start[i] = start;
        p.lvl_len[i] = i < p.nlev ? tn.lens[i] : 0;
        start += p.lvl_len[i];
    }
    const int smem = 1024 + p.nslots * (kSlotBytes + kQBytes) + 2 * 4 * kT * kOStride * 4 + 256 + kMaxSlots * 4 + 16 +
                     2 * kMaxSlots * 8 + 32;
    tree_attn_kernel<<<grid, kThreads, smem>>>(p, mk, mv);
}
```

```cpp
#include <cuda_runtime.h>
#include <cuda_bf16.h>
#include <cuda.h>
#include <stdint.h>

namespace {

constexpr int kBatch = 16, kHeads = 32, kT = 4, kCtx = 2048, kD = 128;
constexpr int kNumHeads = kBatch * kHeads;
constexpr int kTile = 64;
constexpr int kTilesPerHead = kCtx / kTile;
constexpr int kSlotBytes = kTile * kD * 2;
constexpr int kQBytes = kT * kD * 2;
constexpr int kMaxLev = 6;
constexpr int kMaxSlots = 12;
constexpr int kOStride = 136;
constexpr int kPartFloats = 520;
constexpr int kThreads = 192;
constexpr int kTraceBytes = 0;

constexpr uint32_t KIND_WHOLE = 0, KIND_PARK = 1, KIND_FINAL = 2, KIND_PART = 3;
constexpr uint32_t META_FIRST = 1u << 9, META_LAST = 1u << 10;

struct Params {
    const __nv_bfloat16* q;
    const __nv_bfloat16* k;
    const __nv_bfloat16* v;
    const __nv_bfloat16* kt;
    const __nv_bfloat16* vt;
    const __nv_bfloat16* mask;
    __nv_bfloat16* out;
    int pre0;
    int pre1;
    int warm;
    int xb;
    int nw;
    int ns;
    int nlev;
    int npool;
    int look;
    int pfhint;
    int lvl_start[kMaxLev];
    int lvl_len[kMaxLev];
};

__device__ unsigned int g_queue;
__device__ float g_part[kNumHeads * kMaxLev * kPartFloats];
#define TICK(i)
#define STAMP(var)

__device__ __forceinline__ uint32_t smem_u32(const void* p) { return (uint32_t)__cvta_generic_to_shared(p); }
__device__ __forceinline__ void mbar_init(uint32_t bar, uint32_t cnt) {
    asm volatile("mbarrier.init.shared::cta.b64 [%0], %1;" ::"r"(bar), "r"(cnt) : "memory");
}
__device__ __forceinline__ void mbar_arrive(uint32_t bar) {
    asm volatile("mbarrier.arrive.shared::cta.b64 _, [%0];" ::"r"(bar) : "memory");
}
__device__ __forceinline__ void mbar_expect_tx(uint32_t bar, uint32_t bytes) {
    asm volatile("mbarrier.arrive.expect_tx.shared::cta.b64 _, [%0], %1;" ::"r"(bar), "r"(bytes) : "memory");
}
__device__ __forceinline__ bool mbar_try(uint32_t bar, uint32_t parity) {
    uint32_t ok;
    asm volatile(
        "{\n.reg .pred p;\n"
        "mbarrier.try_wait.parity.shared::cta.b64 p, [%1], %2;\n"
        "selp.u32 %0, 1, 0, p;\n}"
        : "=r"(ok) : "r"(bar), "r"(parity) : "memory");
    return ok != 0;
}
__device__ __forceinline__ void mbar_wait(uint32_t bar, uint32_t parity) {
    if (mbar_try(bar, parity)) return;
    const long long t0 = clock64();
    while (!mbar_try(bar, parity)) {
        if (clock64() - t0 > 4000000000LL) __trap();
    }
}
__device__ __forceinline__ void tma_tile(uint32_t dst, const CUtensorMap* map, int row, uint32_t bar, uint64_t pol) {
    asm volatile("cp.async.bulk.tensor.3d.shared::cluster.global.mbarrier::complete_tx::bytes.L2::cache_hint"
                 " [%0], [%1, {%3, %4, %3}], [%2], %5;"
                 ::"r"(dst), "l"(map), "r"(bar), "r"(0), "r"(row), "l"(pol) : "memory");
}
__device__ __forceinline__ void bulk_copy(uint32_t dst, const void* src, uint32_t bytes, uint32_t bar) {
    asm volatile("cp.async.bulk.shared::cluster.global.mbarrier::complete_tx::bytes [%0], [%1], %2, [%3];"
                 ::"r"(dst), "l"(src), "r"(bytes), "r"(bar) : "memory");
}
__device__ __forceinline__ void ldsm4(uint32_t addr, uint32_t (&r)[4]) {
    asm volatile("ldmatrix.sync.aligned.m8n8.x4.shared.b16 {%0,%1,%2,%3}, [%4];"
                 : "=r"(r[0]), "=r"(r[1]), "=r"(r[2]), "=r"(r[3]) : "r"(addr) : "memory");
}
__device__ __forceinline__ void ldsm4_t(uint32_t addr, uint32_t (&r)[4]) {
    asm volatile("ldmatrix.sync.aligned.m8n8.x4.trans.shared.b16 {%0,%1,%2,%3}, [%4];"
                 : "=r"(r[0]), "=r"(r[1]), "=r"(r[2]), "=r"(r[3]) : "r"(addr) : "memory");
}
__device__ __forceinline__ void mma_bf16(float (&c)[4], const uint32_t (&a)[4], uint32_t b0, uint32_t b1) {
    asm volatile("mma.sync.aligned.m16n8k16.row.col.f32.bf16.bf16.f32 {%0,%1,%2,%3}, {%4,%5,%6,%7}, {%8,%9}, {%0,%1,%2,%3};"
                 : "+f"(c[0]), "+f"(c[1]), "+f"(c[2]), "+f"(c[3])
                 : "r"(a[0]), "r"(a[1]), "r"(a[2]), "r"(a[3]), "r"(b0), "r"(b1));
}
__device__ __forceinline__ uint32_t pack_bf16(float lo, float hi) {
    uint32_t r;
    asm("cvt.rn.bf16x2.f32 %0, %1, %2;" : "=r"(r) : "f"(hi), "f"(lo));
    return r;
}
__device__ __forceinline__ uint32_t movmatrix_t(uint32_t a) {
    uint32_t d;
    asm volatile("movmatrix.sync.aligned.m8n8.trans.b16 %0, %1;" : "=r"(d) : "r"(a));
    return d;
}
__device__ __forceinline__ float ex2(float x) {
    float y;
    asm("ex2.approx.ftz.f32 %0, %1;" : "=f"(y) : "f"(x));
    return y;
}
__device__ __forceinline__ float bf_lo(uint32_t v) { return __uint_as_float(v << 16); }
__device__ __forceinline__ float bf_hi(uint32_t v) { return __uint_as_float(v & 0xffff0000u); }
__device__ __forceinline__ float lds_f32(uint32_t a) {
    float v;
    asm volatile("ld.shared.f32 %0, [%1];" : "=f"(v) : "r"(a) : "memory");
    return v;
}
__device__ __forceinline__ uint32_t lds_u32(uint32_t a) {
    uint32_t v;
    asm volatile("ld.shared.u32 %0, [%1];" : "=r"(v) : "r"(a) : "memory");
    return v;
}
__device__ __forceinline__ float4 lds_f32x4(uint32_t a) {
    float4 v;
    asm volatile("ld.shared.v4.f32 {%0,%1,%2,%3}, [%4];" : "=f"(v.x), "=f"(v.y), "=f"(v.z), "=f"(v.w) : "r"(a) : "memory");
    return v;
}
__device__ __forceinline__ void sts_f32(uint32_t a, float v) { asm volatile("st.shared.f32 [%0], %1;" ::"r"(a), "f"(v) : "memory"); }
__device__ __forceinline__ void sts_u32(uint32_t a, uint32_t v) { asm volatile("st.shared.u32 [%0], %1;" ::"r"(a), "r"(v) : "memory"); }

__device__ __forceinline__ uint32_t enc_word(float x) { return max(__float_as_uint(x), 1u); }
__device__ __forceinline__ void st_part(float* p, float a, float b, float c, float d) {
    asm volatile("st.relaxed.gpu.global.v4.b32 [%0], {%1,%2,%3,%4};"
                 ::"l"(p), "r"(enc_word(a)), "r"(enc_word(b)), "r"(enc_word(c)), "r"(enc_word(d)) : "memory");
}
__device__ __forceinline__ void clear_part(float* p) {
    asm volatile("st.relaxed.gpu.global.v4.b32 [%0], {%1,%1,%1,%1};" ::"l"(p), "r"(0u) : "memory");
}
__device__ __forceinline__ void ld_part(const float* p, uint4& v, bool pred) {
    asm volatile("{\n.reg .pred p;\nsetp.ne.u32 p, %5, 0;\n@p ld.relaxed.gpu.global.v4.b32 {%0,%1,%2,%3}, [%4];\n}"
                 : "+r"(v.x), "+r"(v.y), "+r"(v.z), "+r"(v.w) : "l"(p), "r"((uint32_t)pred) : "memory");
}
__device__ __forceinline__ bool all_set(const uint4& v) { return v.x != 0 && v.y != 0 && v.z != 0 && v.w != 0; }
__device__ __forceinline__ float comp(const uint4& v, int i) {
    return __uint_as_float(i == 0 ? v.x : i == 1 ? v.y : i == 2 ? v.z : v.w);
}
__device__ __forceinline__ void prefetch_l2(const void* src, uint32_t bytes) {
    asm volatile("cp.async.bulk.prefetch.L2.global [%0], %1;" ::"l"(src), "r"(bytes) : "memory");
}

__device__ __forceinline__ void prefetch_l2_hint(const void* src, uint32_t bytes, uint64_t pol) {
    asm volatile("cp.async.bulk.prefetch.L2.global.L2::cache_hint [%0], %1, %2;" ::"l"(src), "r"(bytes), "l"(pol) : "memory");
}
__device__ __forceinline__ uint32_t opaque(uint32_t x) { asm volatile("" : "+r"(x)); return x; }

constexpr float kLog2e = 1.4426950408889634f;
constexpr float kScale = 0.08838834764831845f;
constexpr float kScaleLog2e = kScale * kLog2e;

struct RowState {
    float o[kT][4];
    float m[kT];
    float l[kT];
};

__device__ __forceinline__ void tree_part(const Params& p, int head, int lane, RowState& r) {
    const size_t base = (size_t)head * (kT * kD) + 4 * lane;
    uint2 qv[kT], kv[kT], vv[kT];
#pragma unroll
    for (int i = 0; i < kT; i++) {
        qv[i] = __ldg(reinterpret_cast<const uint2*>(p.q + base + i * kD));
        kv[i] = __ldg(reinterpret_cast<const uint2*>(p.kt + base + i * kD));
        vv[i] = __ldg(reinterpret_cast<const uint2*>(p.vt + base + i * kD));
    }
    const uint4* mp = reinterpret_cast<const uint4*>(p.mask + (size_t)(head / kHeads) * (kT * kT));
    const uint4 mk0 = __ldg(mp), mk1 = __ldg(mp + 1);
    const uint32_t mw[8] = {mk0.x, mk0.y, mk0.z, mk0.w, mk1.x, mk1.y, mk1.z, mk1.w};
    float s[kT][kT];
#pragma unroll
    for (int i = 0; i < kT; i++)
#pragma unroll
        for (int j = 0; j < kT; j++) {
            float a = bf_lo(qv[i].x) * bf_lo(kv[j].x);
            a = fmaf(bf_hi(qv[i].x), bf_hi(kv[j].x), a);
            a = fmaf(bf_lo(qv[i].y), bf_lo(kv[j].y), a);
            a = fmaf(bf_hi(qv[i].y), bf_hi(kv[j].y), a);
            s[i][j] = a;
        }
#pragma unroll
    for (int off = 16; off > 0; off >>= 1)
#pragma unroll
        for (int i = 0; i < kT; i++)
#pragma unroll
            for (int j = 0; j < kT; j++) s[i][j] += __shfl_xor_sync(0xffffffffu, s[i][j], off);
#pragma unroll
    for (int i = 0; i < kT; i++) {
        float t[kT];
        float m = -INFINITY;
#pragma unroll
        for (int j = 0; j < kT; j++) {
            const uint32_t w = mw[i * 2 + (j >> 1)];
            const float mk = (j & 1) ? bf_hi(w) : bf_lo(w);
            t[j] = (s[i][j] * kScale + (1.0f - mk) * -1000000000.0f) * kLog2e;
            m = fmaxf(m, t[j]);
        }
        float l = 0.f, o0 = 0.f, o1 = 0.f, o2 = 0.f, o3 = 0.f;
#pragma unroll
        for (int j = 0; j < kT; j++) {
            const float pj = ex2(t[j] - m);
            l += pj;
            o0 = fmaf(pj, bf_lo(vv[j].x), o0);
            o1 = fmaf(pj, bf_hi(vv[j].x), o1);
            o2 = fmaf(pj, bf_lo(vv[j].y), o2);
            o3 = fmaf(pj, bf_hi(vv[j].y), o3);
        }
        r.m[i] = m; r.l[i] = l;
        r.o[i][0] = o0; r.o[i][1] = o1; r.o[i][2] = o2; r.o[i][3] = o3;
    }
}

__device__ __forceinline__ void merge_state(RowState& a, const RowState& b) {
#pragma unroll
    for (int i = 0; i < kT; i++) {
        const float m = fmaxf(a.m[i], b.m[i]);
        const float wa = ex2(a.m[i] - m), wb = ex2(b.m[i] - m);
        a.m[i] = m;
        a.l[i] = a.l[i] * wa + b.l[i] * wb;
#pragma unroll
        for (int e = 0; e < 4; e++) a.o[i][e] = a.o[i][e] * wa + b.o[i][e] * wb;
    }
}

__device__ __forceinline__ void write_out(const Params& p, int head, int lane, const RowState& r) {
#pragma unroll
    for (int i = 0; i < kT; i++) {
        const float inv = __frcp_rn(r.l[i]);
        uint2 v;
        v.x = pack_bf16(r.o[i][0] * inv, r.o[i][1] * inv);
        v.y = pack_bf16(r.o[i][2] * inv, r.o[i][3] * inv);
        *reinterpret_cast<uint2*>(p.out + (size_t)head * (kT * kD) + i * kD + 4 * lane) = v;
    }
}

#define PRO 2
template <int NSLOTS>
__global__ void __launch_bounds__(kThreads, 1)
tree_attn_kernel(const __grid_constant__ Params p, const __grid_constant__ CUtensorMap map_k,
                 const __grid_constant__ CUtensorMap map_v) {
    extern __shared__ __align__(1024) uint8_t smem_raw[];
    const uint32_t smem_base = (smem_u32(smem_raw) + 1023u) & ~1023u;
    const uint32_t s_tile = smem_base;
    const uint32_t s_q = s_tile + NSLOTS * kSlotBytes;
    const uint32_t s_o = s_q + NSLOTS * kQBytes;
    const uint32_t s_ml = s_o + 3 * 4 * kT * kOStride * 4;
    const uint32_t s_home = s_ml + 3 * 4 * 8 * 4;
    const uint32_t s_meta = s_home + kPartFloats * 4;
    const uint32_t s_cmeta = s_meta + kMaxSlots * 4;
    const uint32_t s_full = s_cmeta + 16;
    const uint32_t s_empty = s_full + kMaxSlots * 8;
    const uint32_t s_cfull = s_empty + kMaxSlots * 8;
    const uint32_t s_cempty = s_cfull + 16;
    const uint32_t s_homebar = s_cempty + 16;

    const int warp = threadIdx.x >> 5;
    const int lane = threadIdx.x & 31;
    uint64_t pol = 0;

    if (threadIdx.x == 160) {
#pragma unroll
        for (int i = 0; i < NSLOTS; i++) mbar_init(s_full + i * 8, 1);
        asm volatile("fence.mbarrier_init.release.cluster;" ::: "memory");
        asm volatile("fence.proxy.async.shared::cta;" ::: "memory");
        STAMP(ts_p[0]);
    }
    if (warp == 5) {
        asm volatile("bar.arrive 3, 64;" ::: "memory");
        if (lane == 0) bulk_copy(s_q, p.q + (size_t)blockIdx.x * (kT * kD), kQBytes, s_full);
    }
    if (warp == 4) {
        STAMP(ts_p[4]);
        asm volatile("prefetch.tensormap [%0];" ::"l"(&map_k) : "memory");
        asm volatile("createpolicy.fractional.L2::evict_first.b64 %0, 1.0;" : "=l"(pol));
        STAMP(ts_p[0]);
        asm volatile("bar.sync 3, 64;" ::: "memory");
        if (lane == 0) {
            STAMP(ts_p[1]);
#pragma unroll
            for (int s = 0; s < NSLOTS; s++) {
                mbar_expect_tx(s_full + s * 8, s == 0 ? kSlotBytes + kQBytes : kSlotBytes);
                tma_tile(s_tile + s * kSlotBytes, (s & 1) ? &map_v : &map_k, blockIdx.x * kCtx + (s >> 1) * kTile,
                         s_full + s * 8, pol);
                if (s == 0) STAMP(ts_p[3]);
                if (!(s & 1)) sts_u32(s_meta + s * 4, (KIND_PARK << 11) | blockIdx.x | (s == 0 ? META_FIRST : 0u));
            }
            STAMP(ts_a);
        }
    }
    if (threadIdx.x == 0) {
#pragma unroll
        for (int i = 0; i < NSLOTS; i++) mbar_init(s_empty + i * 8, 4);
        mbar_init(s_cfull, 4); mbar_init(s_cfull + 8, 4);
        mbar_init(s_cempty, 1); mbar_init(s_cempty + 8, 1);
        mbar_init(s_homebar, 1);
    }
    __syncthreads();

    if (warp == 4) {
        if (lane == 0) {
            const unsigned wrap = (unsigned)(p.npool + gridDim.x - 1);
            uint32_t slot = 0, phase = 0;
            int head = blockIdx.x, t0 = 0, n = kTilesPerHead - p.xb, h = NSLOTS;
            uint32_t tag = KIND_PARK << 11;
            while (true) {
                const bool is_final = (tag >> 11 & 3u) == KIND_FINAL;
                const int fetch_at = is_final ? -1 : (n > p.look ? 2 * (n - p.look) : 0);
                unsigned nxt = 0;
                const int row0 = head * kCtx + t0 * kTile;
                for (; h < 2 * n; h++) {
                    if (h == fetch_at) nxt = atomicInc(&g_queue, wrap);
                    mbar_wait(s_empty + slot * 8, phase);
                    const uint32_t bar = s_full + slot * 8;
                    const int row = row0 + (h >> 1) * kTile;
                    if (!(h & 1)) {
                        uint32_t meta = tag | (uint32_t)head;
                        if (h == 0) meta |= META_FIRST;
                        if (h == 2 * n - 2) meta |= META_LAST;
                        sts_u32(s_meta + slot * 4, meta);
                        mbar_expect_tx(bar, h == 0 ? kSlotBytes + kQBytes : kSlotBytes);
                        tma_tile(s_tile + slot * kSlotBytes, &map_k, row, bar, pol);
                        if (h == 0) bulk_copy(s_q + slot * kQBytes, p.q + (size_t)head * (kT * kD), kQBytes, bar);
                    } else {
                        mbar_expect_tx(bar, kSlotBytes);
                        tma_tile(s_tile + slot * kSlotBytes, &map_v, row, bar, pol);
                    }
                    if (++slot == NSLOTS) { slot = 0; phase ^= 1; }
                }
                if (is_final) break;
                h = 0;
                if (nxt < (unsigned)p.nw) {
                    head = gridDim.x + nxt; t0 = 0; n = kTilesPerHead; tag = KIND_WHOLE << 11;
                } else if (nxt < (unsigned)p.npool) {
                    const int r = nxt - p.nw;
                    const int lev = r / p.ns;
                    head = gridDim.x + p.nw + (r - lev * p.ns);
                    t0 = p.lvl_start[lev]; n = p.lvl_len[lev];
                    tag = (KIND_PART << 11) | ((uint32_t)lev << 13);
                } else {
                    head = blockIdx.x; t0 = kTilesPerHead - p.xb; n = p.xb; tag = KIND_FINAL << 11;
                }
            }
        }
    } else if (warp < 4) {
        const int g = lane >> 2, t = lane & 3;
        uint32_t koff[4], voff[4];
        {
            const uint32_t krow = 16 * warp + (lane & 7) + 8 * ((lane >> 3) & 1);
            const uint32_t kx = (lane >> 4) ^ (lane & 7);
            const uint32_t vrow = 16 * warp + (lane & 7) + 8 * (lane >> 4);
            const uint32_t vx = ((lane >> 3) & 1) ^ (lane & 7);
#pragma unroll
            for (int i = 0; i < 4; i++) {
                koff[i] = s_tile + krow * 128 + (((2 * i) ^ kx) << 4);
                voff[i] = s_tile + vrow * 128 + (((2 * i) ^ vx) << 4);
            }
        }
        float o[8][4], po[8][4];
        float m0 = 0.f, m1 = 0.f, l0 = 0.f, l1 = 0.f, pm0 = 0.f, pm1 = 0.f, pl0 = 0.f, pl1 = 0.f;
        uint32_t qf[8][2];
#pragma unroll
        for (int i = 0; i < 8; i++) {
            qf[i][0] = qf[i][1] = 0;
#pragma unroll
            for (int e = 0; e < 4; e++) { o[i][e] = 0.f; po[i][e] = 0.f; }
        }
        uint32_t slot = 0, phase = 0, cbuf = 0, cphase = 1;
        while (true) {
            mbar_wait(s_full + slot * 8, phase);
            const uint32_t meta = lds_u32(s_meta + slot * 4);
            const uint32_t kind = (meta >> 11) & 3u;
            if (meta & META_FIRST) {
                const uint32_t qa = s_q + slot * kQBytes + (g & 3) * (kD * 2) + t * 4;
#pragma unroll
                for (int ks = 0; ks < 8; ks++) {
                    qf[ks][0] = lds_u32(qa + ks * 32);
                    qf[ks][1] = lds_u32(qa + ks * 32 + 16);
                }
                if (kind == KIND_FINAL) {
                    m0 = pm0; m1 = pm1; l0 = pl0; l1 = pl1;
#pragma unroll
                    for (int i = 0; i < 8; i++)
#pragma unroll
                        for (int e = 0; e < 4; e++) o[i][e] = po[i][e];
                } else {
                    m0 = m1 = -INFINITY; l0 = l1 = 0.f;
#pragma unroll
                    for (int i = 0; i < 8; i++)
#pragma unroll
                        for (int e = 0; e < 4; e++) o[i][e] = 0.f;
                }
            }
            float sa[4] = {0.f, 0.f, 0.f, 0.f}, sb[4] = {0.f, 0.f, 0.f, 0.f};
            {
                const uint32_t kb = slot * kSlotBytes;
#pragma unroll
                for (int ks = 0; ks < 8; ks += 2) {
                    uint32_t a0[4], a1[4];
                    ldsm4(koff[ks & 3] + kb + (ks >> 2) * 8192, a0);
                    ldsm4(koff[(ks + 1) & 3] + kb + (ks >> 2) * 8192, a1);
                    mma_bf16(sa, a0, qf[ks][0], qf[ks][1]);
                    mma_bf16(sb, a1, qf[ks + 1][0], qf[ks + 1][1]);
                }
            }
            __syncwarp();
            if (lane == 0) mbar_arrive(s_empty + slot * 8);
            if (++slot == NSLOTS) { slot = 0; phase ^= 1; }

            const float s0 = sa[0] + sb[0], s1 = sa[1] + sb[1], s2 = sa[2] + sb[2], s3 = sa[3] + sb[3];
            float x0 = fmaxf(s0, s2), x1 = fmaxf(s1, s3);
#pragma unroll
            for (int off = 4; off < 32; off <<= 1) {
                x0 = fmaxf(x0, __shfl_xor_sync(0xffffffffu, x0, off));
                x1 = fmaxf(x1, __shfl_xor_sync(0xffffffffu, x1, off));
            }
            const float n0 = fmaxf(m0, x0 * kScaleLog2e), n1 = fmaxf(m1, x1 * kScaleLog2e);
            const float al0 = ex2(m0 - n0), al1 = ex2(m1 - n1);
            m0 = n0; m1 = n1;
            const float p0 = ex2(fmaf(s0, kScaleLog2e, -n0)), p1 = ex2(fmaf(s1, kScaleLog2e, -n1));
            const float p2 = ex2(fmaf(s2, kScaleLog2e, -n0)), p3 = ex2(fmaf(s3, kScaleLog2e, -n1));
            l0 = fmaf(l0, al0, p0 + p2);
            l1 = fmaf(l1, al1, p1 + p3);
            const uint32_t b0 = movmatrix_t(pack_bf16(p0, p1));
            const uint32_t b1 = movmatrix_t(pack_bf16(p2, p3));
#pragma unroll
            for (int i = 0; i < 8; i++) {
                o[i][0] *= al0; o[i][1] *= al1; o[i][2] *= al0; o[i][3] *= al1;
            }
            const bool home_last = (meta & META_LAST) && (kind == KIND_FINAL || (kind == KIND_PARK && (p.warm & 1)));
            float fsc[4] = {0.f, 0.f, 0.f, 0.f};
            float4 facc = make_float4(0.f, 0.f, 0.f, 0.f);
            if (home_last) {
                float r0 = l0, r1 = l1;
#pragma unroll
                for (int off = 4; off < 32; off <<= 1) {
                    r0 += __shfl_xor_sync(0xffffffffu, r0, off);
                    r1 += __shfl_xor_sync(0xffffffffu, r1, off);
                }
                if (lane < 2) {
                    const uint32_t mb = s_ml + (8 + warp) * 32 + lane * 8;
                    sts_f32(mb, m0); sts_f32(mb + 4, m1);
                    sts_f32(mb + 16, r0); sts_f32(mb + 20, r1);
                }
                asm volatile("bar.sync 2, 128;" ::: "memory");
                mbar_wait(s_homebar, 0);
                float mm[5], ll[5];
#pragma unroll
                for (int w = 0; w < 4; w++) {
                    mm[w] = lds_f32(s_ml + (8 + w) * 32 + warp * 4);
                    ll[w] = lds_f32(s_ml + (8 + w) * 32 + 16 + warp * 4);
                }
                mm[4] = lds_f32(s_home + 512 * 4 + warp * 4);
                ll[4] = lds_f32(s_home + 516 * 4 + warp * 4);
                const float4 tv = lds_f32x4(s_home + (warp * kD + 4 * lane) * 4);
                const float m = fmaxf(fmaxf(fmaxf(mm[0], mm[1]), fmaxf(mm[2], mm[3])), mm[4]);
                float l = 0.f;
#pragma unroll
                for (int w = 0; w < 5; w++) {
                    mm[w] = ex2(mm[w] - m);
                    l = fmaf(ll[w], mm[w], l);
                }
                const float inv = __frcp_rn(l);
#pragma unroll
                for (int w = 0; w < 4; w++) fsc[w] = mm[w] * inv;
                const float ts = mm[4] * inv;
                facc = make_float4(tv.x * ts, tv.y * ts, tv.z * ts, tv.w * ts);
            }
            mbar_wait(s_full + slot * 8, phase);
            {
                const uint32_t vb = slot * kSlotBytes;
#pragma unroll
                for (int mt = 0; mt < 8; mt++) {
                    uint32_t a[4];
                    ldsm4_t(voff[mt & 3] + vb + (mt >> 2) * 8192, a);
                    mma_bf16(o[mt], a, b0, b1);
                }
            }
            __syncwarp();
            if (lane == 0) mbar_arrive(s_empty + slot * 8);
            if (++slot == NSLOTS) { slot = 0; phase ^= 1; }

            if (meta & META_LAST) {
                if (kind == KIND_PARK) {
                    pm0 = m0; pm1 = m1; pl0 = l0; pl1 = l1;
#pragma unroll
                    for (int i = 0; i < 8; i++)
#pragma unroll
                        for (int e = 0; e < 4; e++) po[i][e] = o[i][e];
                    if (!home_last) continue;
                }
                if (!home_last) {
#pragma unroll
                    for (int off = 4; off < 32; off <<= 1) {
                        l0 += __shfl_xor_sync(0xffffffffu, l0, off);
                        l1 += __shfl_xor_sync(0xffffffffu, l1, off);
                    }
                    mbar_wait(s_cempty + cbuf * 8, cphase);
                }
                const uint32_t buf = home_last ? 2u : cbuf;
                const uint32_t ob = s_o + (buf * 4 + warp) * (kT * kOStride * 4);
                const int qq = 2 * (t & 1), hi = t >> 1;
                const uint32_t oa = ob + (qq * kOStride + g + 8 * hi) * 4;
#pragma unroll
                for (int mt = 0; mt < 8; mt++) {
                    sts_f32(oa + mt * 64, hi ? o[mt][2] : o[mt][0]);
                    sts_f32(oa + mt * 64 + kOStride * 4, hi ? o[mt][3] : o[mt][1]);
                }
                if (home_last) {
                    asm volatile("bar.sync 2, 128;" ::: "memory");
#pragma unroll
                    for (int w = 0; w < 4; w++) {
                        const float4 v = lds_f32x4(s_o + ((8 + w) * kT * kOStride + warp * kOStride + 4 * lane) * 4);
                        facc.x = fmaf(v.x, fsc[w], facc.x); facc.y = fmaf(v.y, fsc[w], facc.y);
                        facc.z = fmaf(v.z, fsc[w], facc.z); facc.w = fmaf(v.w, fsc[w], facc.w);
                    }
                    uint2 ov;
                    ov.x = pack_bf16(facc.x, facc.y);
                    ov.y = pack_bf16(facc.z, facc.w);
                    if (kind == KIND_FINAL)
                        *reinterpret_cast<uint2*>(p.out + (size_t)blockIdx.x * (kT * kD) + warp * kD + 4 * lane) = ov;
                    STAMP(ts_c);
                    if (kind == KIND_PARK) {
                        asm volatile("bar.sync 2, 128;" ::: "memory");
                        continue;
                    }
                    mbar_wait(s_cempty + cbuf * 8, cphase);
                } else if (lane < 2) {
                    const uint32_t mb = s_ml + (cbuf * 4 + warp) * 32 + lane * 8;
                    sts_f32(mb, m0); sts_f32(mb + 4, m1);
                    sts_f32(mb + 16, l0); sts_f32(mb + 20, l1);
                }
                if (threadIdx.x == 0) sts_u32(s_cmeta + cbuf * 4, meta);
                __syncwarp();
                if (lane == 0) mbar_arrive(s_cfull + cbuf * 8);
                cbuf ^= 1;
                if (cbuf == 0) cphase ^= 1;
                if (kind == KIND_FINAL) break;
            }
        }
    } else {
        uint32_t cbuf = 0, cphase = 0;
        uint32_t dry = opaque(1u);
        const int nprev = p.nlev - 1;
        while (true) {
            uint32_t meta = (KIND_PART << 11) | ((uint32_t)nprev << 13) | blockIdx.x;
            if (!dry) {
                mbar_wait(s_cfull + cbuf * 8, cphase);
                meta = lds_u32(s_cmeta + cbuf * 4);
            }
            const uint32_t kind = (meta >> 11) & 3u;
            if (kind == KIND_FINAL) break;
            const int head = meta & 511u;
            const int piece = (meta >> 13) & 7u;
            RowState r;
            {
                float4 mw[4], lw[4];
#pragma unroll
                for (int w = 0; w < 4; w++) {
                    mw[w] = lds_f32x4(s_ml + (cbuf * 4 + w) * 32);
                    lw[w] = lds_f32x4(s_ml + (cbuf * 4 + w) * 32 + 16);
                }
#pragma unroll
                for (int i = 0; i < kT; i++) {
                    float mm[4], ll[4];
#pragma unroll
                    for (int w = 0; w < 4; w++) {
                        mm[w] = i == 0 ? mw[w].x : i == 1 ? mw[w].y : i == 2 ? mw[w].z : mw[w].w;
                        ll[w] = i == 0 ? lw[w].x : i == 1 ? lw[w].y : i == 2 ? lw[w].z : lw[w].w;
                    }
                    const float m = fmaxf(fmaxf(mm[0], mm[1]), fmaxf(mm[2], mm[3]));
                    float l = 0.f, a0 = 0.f, a1 = 0.f, a2 = 0.f, a3 = 0.f;
#pragma unroll
                    for (int w = 0; w < 4; w++) {
                        const float sc = ex2(mm[w] - m);
                        const float4 v = lds_f32x4(s_o + ((cbuf * 4 + w) * kT * kOStride + i * kOStride + 4 * lane) * 4);
                        l = fmaf(ll[w], sc, l);
                        a0 = fmaf(v.x, sc, a0); a1 = fmaf(v.y, sc, a1); a2 = fmaf(v.z, sc, a2); a3 = fmaf(v.w, sc, a3);
                    }
                    r.m[i] = m; r.l[i] = l;
                    r.o[i][0] = a0; r.o[i][1] = a1; r.o[i][2] = a2; r.o[i][3] = a3;
                }
            }
            if (!dry) {
                __syncwarp();
                if (lane == 0) mbar_arrive(s_cempty + cbuf * 8);
                cbuf ^= 1;
                if (cbuf == 0) cphase ^= 1;
            }
            TICK(0);

            if (dry || kind == KIND_WHOLE || piece == 0) {
                RowState tr;
                tree_part(p, head, lane, tr);
                if (dry) {
#pragma unroll
                    for (int i = 0; i < kT; i++) {
#pragma unroll
                        for (int e = 0; e < 4; e++) sts_f32(s_home + (i * kD + 4 * lane + e) * 4, tr.o[i][e]);
                        if (lane == 0) { sts_f32(s_home + (512 + i) * 4, tr.m[i]); sts_f32(s_home + (516 + i) * 4, tr.l[i]); }
                    }
                    __syncwarp();
                    if (lane == 0) mbar_arrive(s_homebar);
                }
                merge_state(r, tr);
                TICK(1);
            }
            if (dry && !(p.warm & 2)) { dry = 0; continue; }
            if (kind == KIND_PART) {
                float* part = g_part + (size_t)head * (kMaxLev * kPartFloats);
                if (piece < nprev) {
                    float* dst = part + piece * kPartFloats;
#pragma unroll
                    for (int i = 0; i < kT; i++) st_part(dst + i * kD + 4 * lane, r.o[i][0], r.o[i][1], r.o[i][2], r.o[i][3]);
                    if (lane == 0) {
                        st_part(dst + 512, r.m[0], r.m[1], r.m[2], r.m[3]);
                        st_part(dst + 516, r.l[0], r.l[1], r.l[2], r.l[3]);
                    }
                    TICK(3);
                    continue;
                }
                const int nuse = dry ? 0 : nprev;
                uint4 pm[kMaxLev - 1], pl[kMaxLev - 1], pv[kMaxLev - 1][kT];
                for (int tries = 0;; tries++) {
#pragma unroll
                    for (int k = 0; k < kMaxLev - 1; k++) {
                        const float* src = part + k * kPartFloats;
                        const bool on = k < nuse;
                        pm[k] = make_uint4(0xff800000u, 0xff800000u, 0xff800000u, 0xff800000u);
                        pl[k] = make_uint4(1u, 1u, 1u, 1u);
                        ld_part(src + 512, pm[k], on);
                        ld_part(src + 516, pl[k], on);
#pragma unroll
                        for (int i = 0; i < kT; i++) {
                            pv[k][i] = make_uint4(1u, 1u, 1u, 1u);
                            ld_part(src + i * kD + 4 * lane, pv[k][i], on);
                        }
                    }
                    bool ok = true;
#pragma unroll
                    for (int k = 0; k < kMaxLev - 1; k++) {
                        ok &= all_set(pm[k]) && all_set(pl[k]);
#pragma unroll
                        for (int i = 0; i < kT; i++) ok &= all_set(pv[k][i]);
                    }
                    if (__all_sync(0xffffffffu, ok)) break;
                    if (tries > 2000000) __trap();
                }
#pragma unroll
                for (int k = 0; k < kMaxLev - 1; k++) {
                    if (k < nuse) {
                        float* src = part + k * kPartFloats;
#pragma unroll
                        for (int i = 0; i < kT; i++) clear_part(src + i * kD + 4 * lane);
                        if (lane < 2) clear_part(src + 512 + 4 * lane);
                    }
                }
#pragma unroll
                for (int i = 0; i < kT; i++) {
                    float mm[kMaxLev - 1], ll[kMaxLev - 1];
#pragma unroll
                    for (int k = 0; k < kMaxLev - 1; k++) {
                        mm[k] = comp(pm[k], i);
                        ll[k] = comp(pl[k], i);
                    }
                    float m = r.m[i];
#pragma unroll
                    for (int k = 0; k < kMaxLev - 1; k++) m = fmaxf(m, mm[k]);
                    float l = 0.f, a0 = 0.f, a1 = 0.f, a2 = 0.f, a3 = 0.f;
#pragma unroll
                    for (int k = 0; k < kMaxLev - 1; k++) {
                        const float sc = ex2(mm[k] - m);
                        l = fmaf(ll[k], sc, l);
                        a0 = fmaf(comp(pv[k][i], 0), sc, a0); a1 = fmaf(comp(pv[k][i], 1), sc, a1);
                        a2 = fmaf(comp(pv[k][i], 2), sc, a2); a3 = fmaf(comp(pv[k][i], 3), sc, a3);
                    }
                    const float sc = ex2(r.m[i] - m);
                    r.m[i] = m;
                    r.l[i] = fmaf(r.l[i], sc, l);
                    r.o[i][0] = fmaf(r.o[i][0], sc, a0); r.o[i][1] = fmaf(r.o[i][1], sc, a1);
                    r.o[i][2] = fmaf(r.o[i][2], sc, a2); r.o[i][3] = fmaf(r.o[i][3], sc, a3);
                }
            }
            if (!dry) write_out(p, head, lane, r);
            dry = 0;
            TICK(5);
        }
    }
}

typedef CUresult (*EncodeTiledFn)(CUtensorMap*, CUtensorMapDataType, cuuint32_t, void*, const cuuint64_t*,
                                  const cuuint64_t*, const cuuint32_t*, const cuuint32_t*, CUtensorMapInterleave,
                                  CUtensorMapSwizzle, CUtensorMapL2promotion, CUtensorMapFloatOOBfill);

void make_map(EncodeTiledFn enc, CUtensorMap* m, const void* ptr) {
    cuuint64_t dims[3] = {64, (cuuint64_t)kNumHeads * kCtx, 2};
    cuuint64_t strides[2] = {kD * 2, 128};
    cuuint32_t box[3] = {64, (cuuint32_t)kTile, 2};
    cuuint32_t estr[3] = {1, 1, 1};
    enc(m, CU_TENSOR_MAP_DATA_TYPE_BFLOAT16, 3, const_cast<void*>(ptr), dims, strides, box, estr,
        CU_TENSOR_MAP_INTERLEAVE_NONE, CU_TENSOR_MAP_SWIZZLE_128B, CU_TENSOR_MAP_L2_PROMOTION_L2_256B,
        CU_TENSOR_MAP_FLOAT_OOB_FILL_NONE);
}

struct Tuning {
    int nslots = 3;
    int pre0 = 3;
    int pre1 = 0;
    int warm = 3;
    int xb = 4;
    int ns = 132;
    int nlev = 5;
    int lens[kMaxLev] = {16, 8, 4, 2, 2, 0};
    int look = 1;
    int pfhint = 0;
    int grid = 0;
};

}

extern "C" void kernel_launch(void* const* d_in, const int* in_sizes, int n_in, void* d_out, int out_size) {
    (void)in_sizes; (void)n_in; (void)out_size;
    const Tuning tn;
    static EncodeTiledFn enc = nullptr;
    static int num_sms = 0;
    if (!enc) {
        void* fn = nullptr;
        cudaDriverEntryPointQueryResult qr;
        cudaGetDriverEntryPoint("cuTensorMapEncodeTiled", &fn, cudaEnableDefault, &qr);
        enc = (EncodeTiledFn)fn;
        int dev = 0;
        cudaGetDevice(&dev);
        cudaDeviceGetAttribute(&num_sms, cudaDevAttrMultiProcessorCount, dev);
        cudaFuncSetAttribute(tree_attn_kernel<3>, cudaFuncAttributeMaxDynamicSharedMemorySize, 160 * 1024);
    }
    CUtensorMap mk, mv;
    make_map(enc, &mk, d_in[1]);
    make_map(enc, &mv, d_in[2]);

    int grid = tn.grid > 0 ? tn.grid : num_sms;
    if (grid > kNumHeads) grid = kNumHeads;

    Params p;
    p.q = (const __nv_bfloat16*)d_in[0];
    p.k = (const __nv_bfloat16*)d_in[1];
    p.v = (const __nv_bfloat16*)d_in[2];
    p.kt = (const __nv_bfloat16*)d_in[3];
    p.vt = (const __nv_bfloat16*)d_in[4];
    p.mask = (const __nv_bfloat16*)d_in[5];
    p.out = (__nv_bfloat16*)d_out;
    p.pre0 = tn.pre0;
    p.pre1 = tn.pre1;
    p.warm = tn.warm;
    p.xb = tn.xb;
    p.ns = tn.ns < kNumHeads - grid ? tn.ns : kNumHeads - grid;
    p.nw = kNumHeads - grid - p.ns;
    p.nlev = tn.nlev;
    p.npool = p.nw + p.ns * p.nlev;
    p.look = tn.look < 1 ? 1 : tn.look;
    p.pfhint = tn.pfhint;
    int start = 0;
    for (int i = 0; i < kMaxLev; i++) {
        p.lvl_start[i] = start;
        p.lvl_len[i] = i < p.nlev ? tn.lens[i] : 0;
        start += p.lvl_len[i];
    }
    const int smem = 1024 + tn.nslots * (kSlotBytes + kQBytes) + 3 * 4 * kT * kOStride * 4 + 3 * 128 + kPartFloats * 4 +
                     kMaxSlots * 4 + 16 + 2 * kMaxSlots * 8 + 48 + kTraceBytes;
    tree_attn_kernel<3><<<grid, kThreads, smem>>>(p, mk, mv);
}
```

```cpp
#include <cuda_runtime.h>
#include <cuda_bf16.h>
#include <cuda.h>
#include <stdint.h>

namespace {

constexpr int kBatch = 16, kHeads = 32, kT = 4, kCtx = 2048, kD = 128;
constexpr int kNumHeads = kBatch * kHeads;
constexpr int kTile = 64;
constexpr int kTilesPerHead = kCtx / kTile;
constexpr int kSlotBytes = kTile * kD * 2;
constexpr int kQBytes = kT * kD * 2;
constexpr int kSlots = 3;
constexpr int kHomeTail = 4;
constexpr int kSplitHeads = 132;
constexpr int kLevels = 5;
constexpr int kLookAhead = 1;
constexpr int kOStride = 136;
constexpr int kPartFloats = 520;
constexpr int kThreads = 192;

constexpr uint32_t KIND_WHOLE = 0, KIND_PARK = 1, KIND_FINAL = 2, KIND_PART = 3;
constexpr uint32_t META_FIRST = 1u << 9, META_LAST = 1u << 10;

struct Params {
    const __nv_bfloat16* q;
    const __nv_bfloat16* k;
    const __nv_bfloat16* kt;
    const __nv_bfloat16* vt;
    const __nv_bfloat16* mask;
    __nv_bfloat16* out;
    int nw;
    int ns;
    int npool;
};

__host__ __device__ constexpr int level_len(int lev) { return lev < 3 ? 16 >> lev : 2; }
__host__ __device__ constexpr int level_start(int lev) { return lev < 4 ? 32 - (32 >> lev) : 30; }
static_assert(level_start(kLevels - 1) + level_len(kLevels - 1) == kTilesPerHead, "pieces must cover a head");

__device__ unsigned int g_queue;
__device__ float g_part[kNumHeads * (kLevels - 1) * kPartFloats];

__device__ __forceinline__ uint32_t smem_u32(const void* p) { return (uint32_t)__cvta_generic_to_shared(p); }
__device__ __forceinline__ void mbar_init(uint32_t bar, uint32_t cnt) {
    asm volatile("mbarrier.init.shared::cta.b64 [%0], %1;" ::"r"(bar), "r"(cnt) : "memory");
}
__device__ __forceinline__ void mbar_arrive(uint32_t bar) {
    asm volatile("mbarrier.arrive.shared::cta.b64 _, [%0];" ::"r"(bar) : "memory");
}
__device__ __forceinline__ void mbar_expect_tx(uint32_t bar, uint32_t bytes) {
    asm volatile("mbarrier.arrive.expect_tx.shared::cta.b64 _, [%0], %1;" ::"r"(bar), "r"(bytes) : "memory");
}
__device__ __forceinline__ bool mbar_try(uint32_t bar, uint32_t parity) {
    uint32_t ok;
    asm volatile(
        "{\n.reg .pred p;\n"
        "mbarrier.try_wait.parity.shared::cta.b64 p, [%1], %2;\n"
        "selp.u32 %0, 1, 0, p;\n}"
        : "=r"(ok) : "r"(bar), "r"(parity) : "memory");
    return ok != 0;
}
__device__ __forceinline__ void mbar_wait(uint32_t bar, uint32_t parity) {
    if (mbar_try(bar, parity)) return;
    const long long t0 = clock64();
    while (!mbar_try(bar, parity)) {
        if (clock64() - t0 > 4000000000LL) __trap();
    }
}
__device__ __forceinline__ void tma_tile(uint32_t dst, const CUtensorMap* map, int row, uint32_t bar, uint64_t pol) {
    asm volatile("cp.async.bulk.tensor.3d.shared::cluster.global.mbarrier::complete_tx::bytes.L2::cache_hint"
                 " [%0], [%1, {%3, %4, %3}], [%2], %5;"
                 ::"r"(dst), "l"(map), "r"(bar), "r"(0), "r"(row), "l"(pol) : "memory");
}
__device__ __forceinline__ void bulk_copy(uint32_t dst, const void* src, uint32_t bytes, uint32_t bar) {
    asm volatile("cp.async.bulk.shared::cluster.global.mbarrier::complete_tx::bytes [%0], [%1], %2, [%3];"
                 ::"r"(dst), "l"(src), "r"(bytes), "r"(bar) : "memory");
}
__device__ __forceinline__ void ldsm4(uint32_t addr, uint32_t (&r)[4]) {
    asm volatile("ldmatrix.sync.aligned.m8n8.x4.shared.b16 {%0,%1,%2,%3}, [%4];"
                 : "=r"(r[0]), "=r"(r[1]), "=r"(r[2]), "=r"(r[3]) : "r"(addr) : "memory");
}
__device__ __forceinline__ void ldsm4_t(uint32_t addr, uint32_t (&r)[4]) {
    asm volatile("ldmatrix.sync.aligned.m8n8.x4.trans.shared.b16 {%0,%1,%2,%3}, [%4];"
                 : "=r"(r[0]), "=r"(r[1]), "=r"(r[2]), "=r"(r[3]) : "r"(addr) : "memory");
}
__device__ __forceinline__ void mma_bf16(float (&c)[4], const uint32_t (&a)[4], uint32_t b0, uint32_t b1) {
    asm volatile("mma.sync.aligned.m16n8k16.row.col.f32.bf16.bf16.f32 {%0,%1,%2,%3}, {%4,%5,%6,%7}, {%8,%9}, {%0,%1,%2,%3};"
                 : "+f"(c[0]), "+f"(c[1]), "+f"(c[2]), "+f"(c[3])
                 : "r"(a[0]), "r"(a[1]), "r"(a[2]), "r"(a[3]), "r"(b0), "r"(b1));
}
__device__ __forceinline__ uint32_t pack_bf16(float lo, float hi) {
    uint32_t r;
    asm("cvt.rn.bf16x2.f32 %0, %1, %2;" : "=r"(r) : "f"(hi), "f"(lo));
    return r;
}
__device__ __forceinline__ uint32_t movmatrix_t(uint32_t a) {
    uint32_t d;
    asm volatile("movmatrix.sync.aligned.m8n8.trans.b16 %0, %1;" : "=r"(d) : "r"(a));
    return d;
}
__device__ __forceinline__ float ex2(float x) {
    float y;
    asm("ex2.approx.ftz.f32 %0, %1;" : "=f"(y) : "f"(x));
    return y;
}
__device__ __forceinline__ float bf_lo(uint32_t v) { return __uint_as_float(v << 16); }
__device__ __forceinline__ float bf_hi(uint32_t v) { return __uint_as_float(v & 0xffff0000u); }
__device__ __forceinline__ float lds_f32(uint32_t a) {
    float v;
    asm volatile("ld.shared.f32 %0, [%1];" : "=f"(v) : "r"(a) : "memory");
    return v;
}
__device__ __forceinline__ uint32_t lds_u32(uint32_t a) {
    uint32_t v;
    asm volatile("ld.shared.u32 %0, [%1];" : "=r"(v) : "r"(a) : "memory");
    return v;
}
__device__ __forceinline__ float4 lds_f32x4(uint32_t a) {
    float4 v;
    asm volatile("ld.shared.v4.f32 {%0,%1,%2,%3}, [%4];" : "=f"(v.x), "=f"(v.y), "=f"(v.z), "=f"(v.w) : "r"(a) : "memory");
    return v;
}
__device__ __forceinline__ void sts_f32(uint32_t a, float v) { asm volatile("st.shared.f32 [%0], %1;" ::"r"(a), "f"(v) : "memory"); }
__device__ __forceinline__ void sts_u32(uint32_t a, uint32_t v) { asm volatile("st.shared.u32 [%0], %1;" ::"r"(a), "r"(v) : "memory"); }

__device__ __forceinline__ uint32_t enc_word(float x) { return max(__float_as_uint(x), 1u); }
__device__ __forceinline__ void st_part(float* p, float a, float b, float c, float d) {
    asm volatile("st.relaxed.gpu.global.v4.b32 [%0], {%1,%2,%3,%4};"
                 ::"l"(p), "r"(enc_word(a)), "r"(enc_word(b)), "r"(enc_word(c)), "r"(enc_word(d)) : "memory");
}
__device__ __forceinline__ void clear_part(float* p) {
    asm volatile("st.relaxed.gpu.global.v4.b32 [%0], {%1,%1,%1,%1};" ::"l"(p), "r"(0u) : "memory");
}
__device__ __forceinline__ uint4 ld_part(const float* p) {
    uint4 v;
    asm volatile("ld.relaxed.gpu.global.v4.b32 {%0,%1,%2,%3}, [%4];"
                 : "=r"(v.x), "=r"(v.y), "=r"(v.z), "=r"(v.w) : "l"(p) : "memory");
    return v;
}
__device__ __forceinline__ bool all_set(const uint4& v) { return v.x != 0 && v.y != 0 && v.z != 0 && v.w != 0; }
__device__ __forceinline__ float comp(const uint4& v, int i) {
    return __uint_as_float(i == 0 ? v.x : i == 1 ? v.y : i == 2 ? v.z : v.w);
}
__device__ __forceinline__ uint32_t opaque(uint32_t x) { asm volatile("" : "+r"(x)); return x; }

constexpr float kLog2e = 1.4426950408889634f;
constexpr float kScale = 0.08838834764831845f;
constexpr float kScaleLog2e = kScale * kLog2e;

struct RowState {
    float o[kT][4];
    float m[kT];
    float l[kT];
};

__device__ __forceinline__ void tree_part(const Params& p, int head, int lane, RowState& r) {
    const size_t base = (size_t)head * (kT * kD) + 4 * lane;
    uint2 qv[kT], kv[kT], vv[kT];
#pragma unroll
    for (int i = 0; i < kT; i++) {
        qv[i] = __ldg(reinterpret_cast<const uint2*>(p.q + base + i * kD));
        kv[i] = __ldg(reinterpret_cast<const uint2*>(p.kt + base + i * kD));
        vv[i] = __ldg(reinterpret_cast<const uint2*>(p.vt + base + i * kD));
    }
    const uint4* mp = reinterpret_cast<const uint4*>(p.mask + (size_t)(head / kHeads) * (kT * kT));
    const uint4 mk0 = __ldg(mp), mk1 = __ldg(mp + 1);
    const uint32_t mw[8] = {mk0.x, mk0.y, mk0.z, mk0.w, mk1.x, mk1.y, mk1.z, mk1.w};
    float s[kT][kT];
#pragma unroll
    for (int i = 0; i < kT; i++)
#pragma unroll
        for (int j = 0; j < kT; j++) {
            float a = bf_lo(qv[i].x) * bf_lo(kv[j].x);
            a = fmaf(bf_hi(qv[i].x), bf_hi(kv[j].x), a);
            a = fmaf(bf_lo(qv[i].y), bf_lo(kv[j].y), a);
            a = fmaf(bf_hi(qv[i].y), bf_hi(kv[j].y), a);
            s[i][j] = a;
        }
#pragma unroll
    for (int off = 16; off > 0; off >>= 1)
#pragma unroll
        for (int i = 0; i < kT; i++)
#pragma unroll
            for (int j = 0; j < kT; j++) s[i][j] += __shfl_xor_sync(0xffffffffu, s[i][j], off);
#pragma unroll
    for (int i = 0; i < kT; i++) {
        float t[kT];
        float m = -INFINITY;
#pragma unroll
        for (int j = 0; j < kT; j++) {
            const uint32_t w = mw[i * 2 + (j >> 1)];
            const float mk = (j & 1) ? bf_hi(w) : bf_lo(w);
            t[j] = (s[i][j] * kScale + (1.0f - mk) * -1000000000.0f) * kLog2e;
            m = fmaxf(m, t[j]);
        }
        float l = 0.f, o0 = 0.f, o1 = 0.f, o2 = 0.f, o3 = 0.f;
#pragma unroll
        for (int j = 0; j < kT; j++) {
            const float pj = ex2(t[j] - m);
            l += pj;
            o0 = fmaf(pj, bf_lo(vv[j].x), o0);
            o1 = fmaf(pj, bf_hi(vv[j].x), o1);
            o2 = fmaf(pj, bf_lo(vv[j].y), o2);
            o3 = fmaf(pj, bf_hi(vv[j].y), o3);
        }
        r.m[i] = m; r.l[i] = l;
        r.o[i][0] = o0; r.o[i][1] = o1; r.o[i][2] = o2; r.o[i][3] = o3;
    }
}

__device__ __forceinline__ void merge_state(RowState& a, const RowState& b) {
#pragma unroll
    for (int i = 0; i < kT; i++) {
        const float m = fmaxf(a.m[i], b.m[i]);
        const float wa = ex2(a.m[i] - m), wb = ex2(b.m[i] - m);
        a.m[i] = m;
        a.l[i] = a.l[i] * wa + b.l[i] * wb;
#pragma unroll
        for (int e = 0; e < 4; e++) a.o[i][e] = a.o[i][e] * wa + b.o[i][e] * wb;
    }
}

__device__ __forceinline__ void write_out(const Params& p, int head, int lane, const RowState& r) {
#pragma unroll
    for (int i = 0; i < kT; i++) {
        const float inv = __frcp_rn(r.l[i]);
        uint2 v;
        v.x = pack_bf16(r.o[i][0] * inv, r.o[i][1] * inv);
        v.y = pack_bf16(r.o[i][2] * inv, r.o[i][3] * inv);
        *reinterpret_cast<uint2*>(p.out + (size_t)head * (kT * kD) + i * kD + 4 * lane) = v;
    }
}

__global__ void __launch_bounds__(kThreads, 1)
tree_attn_kernel(const __grid_constant__ Params p, const __grid_constant__ CUtensorMap map_k,
                 const __grid_constant__ CUtensorMap map_v) {
    extern __shared__ __align__(1024) uint8_t smem_raw[];
    const uint32_t smem_base = (smem_u32(smem_raw) + 1023u) & ~1023u;
    const uint32_t s_tile = smem_base;
    const uint32_t s_q = s_tile + kSlots * kSlotBytes;
    const uint32_t s_o = s_q + kSlots * kQBytes;
    const uint32_t s_ml = s_o + 3 * 4 * kT * kOStride * 4;
    const uint32_t s_home = s_ml + 3 * 4 * 8 * 4;
    const uint32_t s_meta = s_home + kPartFloats * 4;
    const uint32_t s_cmeta = s_meta + 16;
    const uint32_t s_full = s_cmeta + 16;
    const uint32_t s_empty = s_full + 32;
    const uint32_t s_cfull = s_empty + 32;
    const uint32_t s_cempty = s_cfull + 16;
    const uint32_t s_homebar = s_cempty + 16;

    const int warp = threadIdx.x >> 5;
    const int lane = threadIdx.x & 31;
    uint64_t pol = 0;

    if (warp < 4) {
        const char* pk = reinterpret_cast<const char*>(p.k) + (size_t)blockIdx.x * (kCtx * kD * 2) + threadIdx.x * 128;
        asm volatile("prefetch.global.L2 [%0];" ::"l"(pk) : "memory");
    }
    if (threadIdx.x == 160) {
#pragma unroll
        for (int i = 0; i < kSlots; i++) mbar_init(s_full + i * 8, 1);
        asm volatile("fence.mbarrier_init.release.cluster;" ::: "memory");
        asm volatile("fence.proxy.async.shared::cta;" ::: "memory");
    }
    if (warp == 5) {
        asm volatile("bar.arrive 3, 64;" ::: "memory");
        if (lane == 0) bulk_copy(s_q, p.q + (size_t)blockIdx.x * (kT * kD), kQBytes, s_full);
    }
    if (warp == 4) {
        asm volatile("prefetch.tensormap [%0];" ::"l"(&map_k) : "memory");
        asm volatile("createpolicy.fractional.L2::evict_first.b64 %0, 1.0;" : "=l"(pol));
        asm volatile("bar.sync 3, 64;" ::: "memory");
        if (lane == 0) {
#pragma unroll
            for (int s = 0; s < kSlots; s++) {
                mbar_expect_tx(s_full + s * 8, s == 0 ? kSlotBytes + kQBytes : kSlotBytes);
                tma_tile(s_tile + s * kSlotBytes, (s & 1) ? &map_v : &map_k, blockIdx.x * kCtx + (s >> 1) * kTile,
                         s_full + s * 8, pol);
                if (!(s & 1)) sts_u32(s_meta + s * 4, (KIND_PARK << 11) | blockIdx.x | (s == 0 ? META_FIRST : 0u));
            }
        }
    }
    if (threadIdx.x == 0) {
#pragma unroll
        for (int i = 0; i < kSlots; i++) mbar_init(s_empty + i * 8, 4);
        mbar_init(s_cfull, 4); mbar_init(s_cfull + 8, 4);
        mbar_init(s_cempty, 1); mbar_init(s_cempty + 8, 1);
        mbar_init(s_homebar, 1);
    }
    __syncthreads();

    if (warp == 4) {
        if (lane == 0) {
            const unsigned wrap = (unsigned)(p.npool + gridDim.x - 1);
            uint32_t slot = 0, phase = 0;
            int head = blockIdx.x, t0 = 0, n = kTilesPerHead - kHomeTail, h = kSlots;
            uint32_t tag = KIND_PARK << 11;
            while (true) {
                const bool is_final = (tag >> 11 & 3u) == KIND_FINAL;
                const int fetch_at = is_final ? -1 : (n > kLookAhead ? 2 * (n - kLookAhead) : 0);
                unsigned nxt = 0;
                const int row0 = head * kCtx + t0 * kTile;
                for (; h < 2 * n; h++) {
                    if (h == fetch_at) nxt = atomicInc(&g_queue, wrap);
                    mbar_wait(s_empty + slot * 8, phase);
                    const uint32_t bar = s_full + slot * 8;
                    const int row = row0 + (h >> 1) * kTile;
                    if (!(h & 1)) {
                        uint32_t meta = tag | (uint32_t)head;
                        if (h == 0) meta |= META_FIRST;
                        if (h == 2 * n - 2) meta |= META_LAST;
                        sts_u32(s_meta + slot * 4, meta);
                        mbar_expect_tx(bar, h == 0 ? kSlotBytes + kQBytes : kSlotBytes);
                        tma_tile(s_tile + slot * kSlotBytes, &map_k, row, bar, pol);
                        if (h == 0) bulk_copy(s_q + slot * kQBytes, p.q + (size_t)head * (kT * kD), kQBytes, bar);
                    } else {
                        mbar_expect_tx(bar, kSlotBytes);
                        tma_tile(s_tile + slot * kSlotBytes, &map_v, row, bar, pol);
                    }
                    if (++slot == kSlots) { slot = 0; phase ^= 1; }
                }
                if (is_final) break;
                h = 0;
                if (nxt < (unsigned)p.nw) {
                    head = gridDim.x + nxt; t0 = 0; n = kTilesPerHead; tag = KIND_WHOLE << 11;
                } else if (nxt < (unsigned)p.npool) {
                    const int r = nxt - p.nw;
                    const int lev = r / p.ns;
                    head = gridDim.x + p.nw + (r - lev * p.ns);
                    t0 = level_start(lev); n = level_len(lev);
                    tag = (KIND_PART << 11) | ((uint32_t)lev << 13);
                } else {
                    head = blockIdx.x; t0 = kTilesPerHead - kHomeTail; n = kHomeTail; tag = KIND_FINAL << 11;
                }
            }
        }
    } else if (warp < 4) {
        const int g = lane >> 2, t = lane & 3;
        uint32_t koff[4], voff[4];
        {
            const uint32_t krow = 16 * warp + (lane & 7) + 8 * ((lane >> 3) & 1);
            const uint32_t kx = (lane >> 4) ^ (lane & 7);
            const uint32_t vrow = 16 * warp + (lane & 7) + 8 * (lane >> 4);
            const uint32_t vx = ((lane >> 3) & 1) ^ (lane & 7);
#pragma unroll
            for (int i = 0; i < 4; i++) {
                koff[i] = s_tile + krow * 128 + (((2 * i) ^ kx) << 4);
                voff[i] = s_tile + vrow * 128 + (((2 * i) ^ vx) << 4);
            }
        }
        float o[8][4], po[8][4];
        float m0 = 0.f, m1 = 0.f, l0 = 0.f, l1 = 0.f, pm0 = 0.f, pm1 = 0.f, pl0 = 0.f, pl1 = 0.f;
        uint32_t qf[8][2];
#pragma unroll
        for (int i = 0; i < 8; i++) {
            qf[i][0] = qf[i][1] = 0;
#pragma unroll
            for (int e = 0; e < 4; e++) { o[i][e] = 0.f; po[i][e] = 0.f; }
        }
        uint32_t slot = 0, phase = 0, cbuf = 0, cphase = 1;
        while (true) {
            mbar_wait(s_full + slot * 8, phase);
            const uint32_t meta = lds_u32(s_meta + slot * 4);
            const uint32_t kind = (meta >> 11) & 3u;
            if (meta & META_FIRST) {
                const uint32_t qa = s_q + slot * kQBytes + (g & 3) * (kD * 2) + t * 4;
#pragma unroll
                for (int ks = 0; ks < 8; ks++) {
                    qf[ks][0] = lds_u32(qa + ks * 32);
                    qf[ks][1] = lds_u32(qa + ks * 32 + 16);
                }
                if (kind == KIND_FINAL) {
                    m0 = pm0; m1 = pm1; l0 = pl0; l1 = pl1;
#pragma unroll
                    for (int i = 0; i < 8; i++)
#pragma unroll
                        for (int e = 0; e < 4; e++) o[i][e] = po[i][e];
                } else {
                    m0 = m1 = -INFINITY; l0 = l1 = 0.f;
#pragma unroll
                    for (int i = 0; i < 8; i++)
#pragma unroll
                        for (int e = 0; e < 4; e++) o[i][e] = 0.f;
                }
            }
            float sa[4] = {0.f, 0.f, 0.f, 0.f}, sb[4] = {0.f, 0.f, 0.f, 0.f};
            {
                const uint32_t kb = slot * kSlotBytes;
#pragma unroll
                for (int ks = 0; ks < 8; ks += 2) {
                    uint32_t a0[4], a1[4];
                    ldsm4(koff[ks & 3] + kb + (ks >> 2) * 8192, a0);
                    ldsm4(koff[(ks + 1) & 3] + kb + (ks >> 2) * 8192, a1);
                    mma_bf16(sa, a0, qf[ks][0], qf[ks][1]);
                    mma_bf16(sb, a1, qf[ks + 1][0], qf[ks + 1][1]);
                }
            }
            __syncwarp();
            if (lane == 0) mbar_arrive(s_empty + slot * 8);
            if (++slot == kSlots) { slot = 0; phase ^= 1; }

            const float s0 = sa[0] + sb[0], s1 = sa[1] + sb[1], s2 = sa[2] + sb[2], s3 = sa[3] + sb[3];
            float x0 = fmaxf(s0, s2), x1 = fmaxf(s1, s3);
#pragma unroll
            for (int off = 4; off < 32; off <<= 1) {
                x0 = fmaxf(x0, __shfl_xor_sync(0xffffffffu, x0, off));
                x1 = fmaxf(x1, __shfl_xor_sync(0xffffffffu, x1, off));
            }
            const float n0 = fmaxf(m0, x0 * kScaleLog2e), n1 = fmaxf(m1, x1 * kScaleLog2e);
            const float al0 = ex2(m0 - n0), al1 = ex2(m1 - n1);
            m0 = n0; m1 = n1;
            const float p0 = ex2(fmaf(s0, kScaleLog2e, -n0)), p1 = ex2(fmaf(s1, kScaleLog2e, -n1));
            const float p2 = ex2(fmaf(s2, kScaleLog2e, -n0)), p3 = ex2(fmaf(s3, kScaleLog2e, -n1));
            l0 = fmaf(l0, al0, p0 + p2);
            l1 = fmaf(l1, al1, p1 + p3);
            const uint32_t b0 = movmatrix_t(pack_bf16(p0, p1));
            const uint32_t b1 = movmatrix_t(pack_bf16(p2, p3));
#pragma unroll
            for (int i = 0; i < 8; i++) {
                o[i][0] *= al0; o[i][1] *= al1; o[i][2] *= al0; o[i][3] *= al1;
            }
            const bool home_last = (meta & META_LAST) && kind == KIND_FINAL;
            float fsc[4] = {0.f, 0.f, 0.f, 0.f};
            float4 facc = make_float4(0.f, 0.f, 0.f, 0.f);
            if (home_last) {
                float r0 = l0, r1 = l1;
#pragma unroll
                for (int off = 4; off < 32; off <<= 1) {
                    r0 += __shfl_xor_sync(0xffffffffu, r0, off);
                    r1 += __shfl_xor_sync(0xffffffffu, r1, off);
                }
                if (lane < 2) {
                    const uint32_t mb = s_ml + (8 + warp) * 32 + lane * 8;
                    sts_f32(mb, m0); sts_f32(mb + 4, m1);
                    sts_f32(mb + 16, r0); sts_f32(mb + 20, r1);
                }
                asm volatile("bar.sync 2, 128;" ::: "memory");
                mbar_wait(s_homebar, 0);
                float mm[5], ll[5];
#pragma unroll
                for (int w = 0; w < 4; w++) {
                    mm[w] = lds_f32(s_ml + (8 + w) * 32 + warp * 4);
                    ll[w] = lds_f32(s_ml + (8 + w) * 32 + 16 + warp * 4);
                }
                mm[4] = lds_f32(s_home + 512 * 4 + warp * 4);
                ll[4] = lds_f32(s_home + 516 * 4 + warp * 4);
                const float4 tv = lds_f32x4(s_home + (warp * kD + 4 * lane) * 4);
                const float m = fmaxf(fmaxf(fmaxf(mm[0], mm[1]), fmaxf(mm[2], mm[3])), mm[4]);
                float l = 0.f;
#pragma unroll
                for (int w = 0; w < 5; w++) {
                    mm[w] = ex2(mm[w] - m);
                    l = fmaf(ll[w], mm[w], l);
                }
                const float inv = __frcp_rn(l);
#pragma unroll
                for (int w = 0; w < 4; w++) fsc[w] = mm[w] * inv;
                const float ts = mm[4] * inv;
                facc = make_float4(tv.x * ts, tv.y * ts, tv.z * ts, tv.w * ts);
            }
            mbar_wait(s_full + slot * 8, phase);
            {
                const uint32_t vb = slot * kSlotBytes;
#pragma unroll
                for (int mt = 0; mt < 8; mt++) {
                    uint32_t a[4];
                    ldsm4_t(voff[mt & 3] + vb + (mt >> 2) * 8192, a);
                    mma_bf16(o[mt], a, b0, b1);
                }
            }
            __syncwarp();
            if (lane == 0) mbar_arrive(s_empty + slot * 8);
            if (++slot == kSlots) { slot = 0; phase ^= 1; }

            if (meta & META_LAST) {
                if (kind == KIND_PARK) {
                    pm0 = m0; pm1 = m1; pl0 = l0; pl1 = l1;
#pragma unroll
                    for (int i = 0; i < 8; i++)
#pragma unroll
                        for (int e = 0; e < 4; e++) po[i][e] = o[i][e];
                    continue;
                }
                if (!home_last) {
#pragma unroll
                    for (int off = 4; off < 32; off <<= 1) {
                        l0 += __shfl_xor_sync(0xffffffffu, l0, off);
                        l1 += __shfl_xor_sync(0xffffffffu, l1, off);
                    }
                    mbar_wait(s_cempty + cbuf * 8, cphase);
                }
                const uint32_t buf = home_last ? 2u : cbuf;
                const uint32_t ob = s_o + (buf * 4 + warp) * (kT * kOStride * 4);
                const int qq = 2 * (t & 1), hi = t >> 1;
                const uint32_t oa = ob + (qq * kOStride + g + 8 * hi) * 4;
#pragma unroll
                for (int mt = 0; mt < 8; mt++) {
                    sts_f32(oa + mt * 64, hi ? o[mt][2] : o[mt][0]);
                    sts_f32(oa + mt * 64 + kOStride * 4, hi ? o[mt][3] : o[mt][1]);
                }
                if (home_last) {
                    asm volatile("bar.sync 2, 128;" ::: "memory");
#pragma unroll
                    for (int w = 0; w < 4; w++) {
                        const float4 v = lds_f32x4(s_o + ((8 + w) * kT * kOStride + warp * kOStride + 4 * lane) * 4);
                        facc.x = fmaf(v.x, fsc[w], facc.x); facc.y = fmaf(v.y, fsc[w], facc.y);
                        facc.z = fmaf(v.z, fsc[w], facc.z); facc.w = fmaf(v.w, fsc[w], facc.w);
                    }
                    uint2 ov;
                    ov.x = pack_bf16(facc.x, facc.y);
                    ov.y = pack_bf16(facc.z, facc.w);
                    *reinterpret_cast<uint2*>(p.out + (size_t)blockIdx.x * (kT * kD) + warp * kD + 4 * lane) = ov;
                    mbar_wait(s_cempty + cbuf * 8, cphase);
                } else if (lane < 2) {
                    const uint32_t mb = s_ml + (cbuf * 4 + warp) * 32 + lane * 8;
                    sts_f32(mb, m0); sts_f32(mb + 4, m1);
                    sts_f32(mb + 16, l0); sts_f32(mb + 20, l1);
                }
                if (threadIdx.x == 0) sts_u32(s_cmeta + cbuf * 4, meta);
                __syncwarp();
                if (lane == 0) mbar_arrive(s_cfull + cbuf * 8);
                cbuf ^= 1;
                if (cbuf == 0) cphase ^= 1;
                if (kind == KIND_FINAL) break;
            }
        }
    } else {
        uint32_t cbuf = 0, cphase = 0;
        uint32_t dry = opaque(1u);
        constexpr int nprev = kLevels - 1;
        while (true) {
            uint32_t meta = (KIND_PART << 11) | ((uint32_t)nprev << 13) | blockIdx.x;
            if (!dry) {
                mbar_wait(s_cfull + cbuf * 8, cphase);
                meta = lds_u32(s_cmeta + cbuf * 4);
            }
            const uint32_t kind = (meta >> 11) & 3u;
            if (kind == KIND_FINAL) break;
            const int head = meta & 511u;
            const int piece = (meta >> 13) & 7u;
            RowState r;
            {
                float4 mw[4], lw[4];
#pragma unroll
                for (int w = 0; w < 4; w++) {
                    mw[w] = lds_f32x4(s_ml + (cbuf * 4 + w) * 32);
                    lw[w] = lds_f32x4(s_ml + (cbuf * 4 + w) * 32 + 16);
                }
#pragma unroll
                for (int i = 0; i < kT; i++) {
                    float mm[4], ll[4];
#pragma unroll
                    for (int w = 0; w < 4; w++) {
                        mm[w] = i == 0 ? mw[w].x : i == 1 ? mw[w].y : i == 2 ? mw[w].z : mw[w].w;
                        ll[w] = i == 0 ? lw[w].x : i == 1 ? lw[w].y : i == 2 ? lw[w].z : lw[w].w;
                    }
                    const float m = fmaxf(fmaxf(mm[0], mm[1]), fmaxf(mm[2], mm[3]));
                    float l = 0.f, a0 = 0.f, a1 = 0.f, a2 = 0.f, a3 = 0.f;
#pragma unroll
                    for (int w = 0; w < 4; w++) {
                        const float sc = ex2(mm[w] - m);
                        const float4 v = lds_f32x4(s_o + ((cbuf * 4 + w) * kT * kOStride + i * kOStride + 4 * lane) * 4);
                        l = fmaf(ll[w], sc, l);
                        a0 = fmaf(v.x, sc, a0); a1 = fmaf(v.y, sc, a1); a2 = fmaf(v.z, sc, a2); a3 = fmaf(v.w, sc, a3);
                    }
                    r.m[i] = m; r.l[i] = l;
                    r.o[i][0] = a0; r.o[i][1] = a1; r.o[i][2] = a2; r.o[i][3] = a3;
                }
            }
            if (!dry) {
                __syncwarp();
                if (lane == 0) mbar_arrive(s_cempty + cbuf * 8);
                cbuf ^= 1;
                if (cbuf == 0) cphase ^= 1;
            }

            if (dry || kind == KIND_WHOLE || piece == 0) {
                RowState tr;
                tree_part(p, head, lane, tr);
                if (dry) {
#pragma unroll
                    for (int i = 0; i < kT; i++) {
#pragma unroll
                        for (int e = 0; e < 4; e++) sts_f32(s_home + (i * kD + 4 * lane + e) * 4, tr.o[i][e]);
                        if (lane == 0) { sts_f32(s_home + (512 + i) * 4, tr.m[i]); sts_f32(s_home + (516 + i) * 4, tr.l[i]); }
                    }
                    __syncwarp();
                    if (lane == 0) mbar_arrive(s_homebar);
                }
                merge_state(r, tr);
            }
            if (dry) { dry = 0; continue; }
            if (kind == KIND_PART) {
                float* part = g_part + (size_t)head * (nprev * kPartFloats);
                if (piece < nprev) {
                    float* dst = part + piece * kPartFloats;
#pragma unroll
                    for (int i = 0; i < kT; i++) st_part(dst + i * kD + 4 * lane, r.o[i][0], r.o[i][1], r.o[i][2], r.o[i][3]);
                    if (lane == 0) {
                        st_part(dst + 512, r.m[0], r.m[1], r.m[2], r.m[3]);
                        st_part(dst + 516, r.l[0], r.l[1], r.l[2], r.l[3]);
                    }
                    continue;
                }
                uint4 pm[nprev], pl[nprev], pv[nprev][kT];
                for (int tries = 0;; tries++) {
#pragma unroll
                    for (int k = 0; k < nprev; k++) {
                        const float* src = part + k * kPartFloats;
                        pm[k] = ld_part(src + 512);
                        pl[k] = ld_part(src + 516);
#pragma unroll
                        for (int i = 0; i < kT; i++) pv[k][i] = ld_part(src + i * kD + 4 * lane);
                    }
                    bool ok = true;
#pragma unroll
                    for (int k = 0; k < nprev; k++) {
                        ok &= all_set(pm[k]) && all_set(pl[k]);
#pragma unroll
                        for (int i = 0; i < kT; i++) ok &= all_set(pv[k][i]);
                    }
                    if (__all_sync(0xffffffffu, ok)) break;
                    if (tries > 2000000) __trap();
                }
#pragma unroll
                for (int k = 0; k < nprev; k++) {
                    float* src = part + k * kPartFloats;
#pragma unroll
                    for (int i = 0; i < kT; i++) clear_part(src + i * kD + 4 * lane);
                    if (lane < 2) clear_part(src + 512 + 4 * lane);
                }
#pragma unroll
                for (int i = 0; i < kT; i++) {
                    float mm[nprev], ll[nprev];
#pragma unroll
                    for (int k = 0; k < nprev; k++) {
                        mm[k] = comp(pm[k], i);
                        ll[k] = comp(pl[k], i);
                    }
                    float m = r.m[i];
#pragma unroll
                    for (int k = 0; k < nprev; k++) m = fmaxf(m, mm[k]);
                    float l = 0.f, a0 = 0.f, a1 = 0.f, a2 = 0.f, a3 = 0.f;
#pragma unroll
                    for (int k = 0; k < nprev; k++) {
                        const float sc = ex2(mm[k] - m);
                        l = fmaf(ll[k], sc, l);
                        a0 = fmaf(comp(pv[k][i], 0), sc, a0); a1 = fmaf(comp(pv[k][i], 1), sc, a1);
                        a2 = fmaf(comp(pv[k][i], 2), sc, a2); a3 = fmaf(comp(pv[k][i], 3), sc, a3);
                    }
                    const float sc = ex2(r.m[i] - m);
                    r.m[i] = m;
                    r.l[i] = fmaf(r.l[i], sc, l);
                    r.o[i][0] = fmaf(r.o[i][0], sc, a0); r.o[i][1] = fmaf(r.o[i][1], sc, a1);
                    r.o[i][2] = fmaf(r.o[i][2], sc, a2); r.o[i][3] = fmaf(r.o[i][3], sc, a3);
                }
            }
            write_out(p, head, lane, r);
        }
    }
}

typedef CUresult (*EncodeTiledFn)(CUtensorMap*, CUtensorMapDataType, cuuint32_t, void*, const cuuint64_t*,
                                  const cuuint64_t*, const cuuint32_t*, const cuuint32_t*, CUtensorMapInterleave,
                                  CUtensorMapSwizzle, CUtensorMapL2promotion, CUtensorMapFloatOOBfill);

void make_map(EncodeTiledFn enc, CUtensorMap* m, const void* ptr) {
    cuuint64_t dims[3] = {64, (cuuint64_t)kNumHeads * kCtx, 2};
    cuuint64_t strides[2] = {kD * 2, 128};
    cuuint32_t box[3] = {64, (cuuint32_t)kTile, 2};
    cuuint32_t estr[3] = {1, 1, 1};
    enc(m, CU_TENSOR_MAP_DATA_TYPE_BFLOAT16, 3, const_cast<void*>(ptr), dims, strides, box, estr,
        CU_TENSOR_MAP_INTERLEAVE_NONE, CU_TENSOR_MAP_SWIZZLE_128B, CU_TENSOR_MAP_L2_PROMOTION_L2_256B,
        CU_TENSOR_MAP_FLOAT_OOB_FILL_NONE);
}

constexpr int kSmemBytes = 1024 + kSlots * (kSlotBytes + kQBytes) + 3 * 4 * kT * kOStride * 4 + 3 * 4 * 8 * 4 +
                           kPartFloats * 4 + 16 + 16 + 32 + 32 + 16 + 16 + 16;

}

extern "C" void kernel_launch(void* const* d_in, const int* in_sizes, int n_in, void* d_out, int out_size) {
    (void)in_sizes; (void)n_in; (void)out_size;
    static EncodeTiledFn enc = nullptr;
    static int num_sms = 0;
    if (!enc) {
        void* fn = nullptr;
        cudaDriverEntryPointQueryResult qr;
        cudaGetDriverEntryPoint("cuTensorMapEncodeTiled", &fn, cudaEnableDefault, &qr);
        enc = (EncodeTiledFn)fn;
        int dev = 0;
        cudaGetDevice(&dev);
        cudaDeviceGetAttribute(&num_sms, cudaDevAttrMultiProcessorCount, dev);
        cudaFuncSetAttribute(tree_attn_kernel, cudaFuncAttributeMaxDynamicSharedMemorySize, kSmemBytes);
    }
    CUtensorMap mk, mv;
    make_map(enc, &mk, d_in[1]);
    make_map(enc, &mv, d_in[2]);

    const int grid = num_sms < kNumHeads ? num_sms : kNumHeads;

    Params p;
    p.q = (const __nv_bfloat16*)d_in[0];
    p.k = (const __nv_bfloat16*)d_in[1];
    p.kt = (const __nv_bfloat16*)d_in[3];
    p.vt = (const __nv_bfloat16*)d_in[4];
    p.mask = (const __nv_bfloat16*)d_in[5];
    p.out = (__nv_bfloat16*)d_out;
    p.ns = kSplitHeads < kNumHeads - grid ? kSplitHeads : kNumHeads - grid;
    p.nw = kNumHeads - grid - p.ns;
    p.npool = p.nw + p.ns * kLevels;
    tree_attn_kernel<<<grid, kThreads, kSmemBytes>>>(p, mk, mv);
}
```

```cpp
#include <cuda_runtime.h>
#include <cuda_bf16.h>
#include <cuda.h>
#include <stdint.h>

namespace {

constexpr int kBatch = 16, kHeads = 32, kT = 4, kCtx = 2048, kD = 128;
constexpr int kNumHeads = kBatch * kHeads;
constexpr int kTile = 64;
constexpr int kTilesPerHead = kCtx / kTile;
constexpr int kSlotBytes = kTile * kD * 2;
constexpr int kQBytes = kT * kD * 2;
constexpr int kSlots = 3;
constexpr int kHomeTail = 4;
constexpr int kSplitHeads = 132;
constexpr int kLevels = 5;
constexpr int kLookAhead = 1;
constexpr int kOStride = 136;
constexpr int kPartFloats = 520;
constexpr int kThreads = 192;

constexpr uint32_t KIND_WHOLE = 0, KIND_PARK = 1, KIND_FINAL = 2, KIND_PART = 3;
constexpr uint32_t META_FIRST = 1u << 9, META_LAST = 1u << 10;

struct Params {
    const __nv_bfloat16* q;
    const __nv_bfloat16* k;
    const __nv_bfloat16* kt;
    const __nv_bfloat16* vt;
    const __nv_bfloat16* mask;
    __nv_bfloat16* out;
    int nw;
    int ns;
    int npool;
};

__host__ __device__ constexpr int level_len(int lev) { return lev < 3 ? 16 >> lev : 2; }
__host__ __device__ constexpr int level_start(int lev) { return lev < 4 ? 32 - (32 >> lev) : 30; }
static_assert(level_start(kLevels - 1) + level_len(kLevels - 1) == kTilesPerHead, "pieces must cover a head");

__device__ unsigned int g_queue;
__device__ float g_part[kNumHeads * (kLevels - 1) * kPartFloats];

__device__ __forceinline__ uint32_t smem_u32(const void* p) { return (uint32_t)__cvta_generic_to_shared(p); }
__device__ __forceinline__ void mbar_init(uint32_t bar, uint32_t cnt) {
    asm volatile("mbarrier.init.shared::cta.b64 [%0], %1;" ::"r"(bar), "r"(cnt) : "memory");
}
__device__ __forceinline__ void mbar_arrive(uint32_t bar) {
    asm volatile("mbarrier.arrive.shared::cta.b64 _, [%0];" ::"r"(bar) : "memory");
}
__device__ __forceinline__ void mbar_expect_tx(uint32_t bar, uint32_t bytes) {
    asm volatile("mbarrier.arrive.expect_tx.shared::cta.b64 _, [%0], %1;" ::"r"(bar), "r"(bytes) : "memory");
}
__device__ __forceinline__ bool mbar_try(uint32_t bar, uint32_t parity) {
    uint32_t ok;
    asm volatile(
        "{\n.reg .pred p;\n"
        "mbarrier.try_wait.parity.shared::cta.b64 p, [%1], %2;\n"
        "selp.u32 %0, 1, 0, p;\n}"
        : "=r"(ok) : "r"(bar), "r"(parity) : "memory");
    return ok != 0;
}
__device__ __forceinline__ void mbar_wait(uint32_t bar, uint32_t parity) {
    if (mbar_try(bar, parity)) return;
    const long long t0 = clock64();
    while (!mbar_try(bar, parity)) {
        if (clock64() - t0 > 4000000000LL) __trap();
    }
}
__device__ __forceinline__ void tma_tile(uint32_t dst, const CUtensorMap* map, int row, uint32_t bar, uint64_t pol) {
    asm volatile("cp.async.bulk.tensor.3d.shared::cluster.global.mbarrier::complete_tx::bytes.L2::cache_hint"
                 " [%0], [%1, {%3, %4, %3}], [%2], %5;"
                 ::"r"(dst), "l"(map), "r"(bar), "r"(0), "r"(row), "l"(pol) : "memory");
}
__device__ __forceinline__ void bulk_copy(uint32_t dst, const void* src, uint32_t bytes, uint32_t bar) {
    asm volatile("cp.async.bulk.shared::cluster.global.mbarrier::complete_tx::bytes [%0], [%1], %2, [%3];"
                 ::"r"(dst), "l"(src), "r"(bytes), "r"(bar) : "memory");
}
__device__ __forceinline__ void ldsm4(uint32_t addr, uint32_t (&r)[4]) {
    asm volatile("ldmatrix.sync.aligned.m8n8.x4.shared.b16 {%0,%1,%2,%3}, [%4];"
                 : "=r"(r[0]), "=r"(r[1]), "=r"(r[2]), "=r"(r[3]) : "r"(addr) : "memory");
}
__device__ __forceinline__ void ldsm4_t(uint32_t addr, uint32_t (&r)[4]) {
    asm volatile("ldmatrix.sync.aligned.m8n8.x4.trans.shared.b16 {%0,%1,%2,%3}, [%4];"
                 : "=r"(r[0]), "=r"(r[1]), "=r"(r[2]), "=r"(r[3]) : "r"(addr) : "memory");
}
__device__ __forceinline__ void mma_bf16(float (&c)[4], const uint32_t (&a)[4], uint32_t b0, uint32_t b1) {
    asm volatile("mma.sync.aligned.m16n8k16.row.col.f32.bf16.bf16.f32 {%0,%1,%2,%3}, {%4,%5,%6,%7}, {%8,%9}, {%0,%1,%2,%3};"
                 : "+f"(c[0]), "+f"(c[1]), "+f"(c[2]), "+f"(c[3])
                 : "r"(a[0]), "r"(a[1]), "r"(a[2]), "r"(a[3]), "r"(b0), "r"(b1));
}
__device__ __forceinline__ uint32_t pack_bf16(float lo, float hi) {
    uint32_t r;
    asm("cvt.rn.bf16x2.f32 %0, %1, %2;" : "=r"(r) : "f"(hi), "f"(lo));
    return r;
}
__device__ __forceinline__ uint32_t movmatrix_t(uint32_t a) {
    uint32_t d;
    asm volatile("movmatrix.sync.aligned.m8n8.trans.b16 %0, %1;" : "=r"(d) : "r"(a));
    return d;
}
__device__ __forceinline__ float ex2(float x) {
    float y;
    asm("ex2.approx.ftz.f32 %0, %1;" : "=f"(y) : "f"(x));
    return y;
}
__device__ __forceinline__ float bf_lo(uint32_t v) { return __uint_as_float(v << 16); }
__device__ __forceinline__ float bf_hi(uint32_t v) { return __uint_as_float(v & 0xffff0000u); }
__device__ __forceinline__ float lds_f32(uint32_t a) {
    float v;
    asm volatile("ld.shared.f32 %0, [%1];" : "=f"(v) : "r"(a) : "memory");
    return v;
}
__device__ __forceinline__ uint32_t lds_u32(uint32_t a) {
    uint32_t v;
    asm volatile("ld.shared.u32 %0, [%1];" : "=r"(v) : "r"(a) : "memory");
    return v;
}
__device__ __forceinline__ float4 lds_f32x4(uint32_t a) {
    float4 v;
    asm volatile("ld.shared.v4.f32 {%0,%1,%2,%3}, [%4];" : "=f"(v.x), "=f"(v.y), "=f"(v.z), "=f"(v.w) : "r"(a) : "memory");
    return v;
}
__device__ __forceinline__ void sts_f32(uint32_t a, float v) { asm volatile("st.shared.f32 [%0], %1;" ::"r"(a), "f"(v) : "memory"); }
__device__ __forceinline__ void sts_u32(uint32_t a, uint32_t v) { asm volatile("st.shared.u32 [%0], %1;" ::"r"(a), "r"(v) : "memory"); }

__device__ __forceinline__ uint32_t enc_word(float x) { return max(__float_as_uint(x), 1u); }
__device__ __forceinline__ void st_part(float* p, float a, float b, float c, float d) {
    asm volatile("st.relaxed.gpu.global.v4.b32 [%0], {%1,%2,%3,%4};"
                 ::"l"(p), "r"(enc_word(a)), "r"(enc_word(b)), "r"(enc_word(c)), "r"(enc_word(d)) : "memory");
}
__device__ __forceinline__ void clear_part(float* p) {
    asm volatile("st.relaxed.gpu.global.v4.b32 [%0], {%1,%1,%1,%1};" ::"l"(p), "r"(0u) : "memory");
}
__device__ __forceinline__ uint4 ld_part(const float* p) {
    uint4 v;
    asm volatile("ld.relaxed.gpu.global.v4.b32 {%0,%1,%2,%3}, [%4];"
                 : "=r"(v.x), "=r"(v.y), "=r"(v.z), "=r"(v.w) : "l"(p) : "memory");
    return v;
}
__device__ __forceinline__ bool all_set(const uint4& v) { return v.x != 0 && v.y != 0 && v.z != 0 && v.w != 0; }
__device__ __forceinline__ float comp(const uint4& v, int i) {
    return __uint_as_float(i == 0 ? v.x : i == 1 ? v.y : i == 2 ? v.z : v.w);
}
__device__ __forceinline__ uint32_t opaque(uint32_t x) { asm volatile("" : "+r"(x)); return x; }

constexpr float kLog2e = 1.4426950408889634f;
constexpr float kScale = 0.08838834764831845f;
constexpr float kScaleLog2e = kScale * kLog2e;

struct RowState {
    float o[kT][4];
    float m[kT];
    float l[kT];
};

__device__ __forceinline__ void tree_part(const Params& p, int head, int lane, RowState& r) {
    const size_t base = (size_t)head * (kT * kD) + 4 * lane;
    uint2 qv[kT], kv[kT], vv[kT];
#pragma unroll
    for (int i = 0; i < kT; i++) {
        qv[i] = __ldg(reinterpret_cast<const uint2*>(p.q + base + i * kD));
        kv[i] = __ldg(reinterpret_cast<const uint2*>(p.kt + base + i * kD));
        vv[i] = __ldg(reinterpret_cast<const uint2*>(p.vt + base + i * kD));
    }
    const uint4* mp = reinterpret_cast<const uint4*>(p.mask + (size_t)(head / kHeads) * (kT * kT));
    const uint4 mk0 = __ldg(mp), mk1 = __ldg(mp + 1);
    const uint32_t mw[8] = {mk0.x, mk0.y, mk0.z, mk0.w, mk1.x, mk1.y, mk1.z, mk1.w};
    float s[kT][kT];
#pragma unroll
    for (int i = 0; i < kT; i++)
#pragma unroll
        for (int j = 0; j < kT; j++) {
            float a = bf_lo(qv[i].x) * bf_lo(kv[j].x);
            a = fmaf(bf_hi(qv[i].x), bf_hi(kv[j].x), a);
            a = fmaf(bf_lo(qv[i].y), bf_lo(kv[j].y), a);
            a = fmaf(bf_hi(qv[i].y), bf_hi(kv[j].y), a);
            s[i][j] = a;
        }
#pragma unroll
    for (int off = 16; off > 0; off >>= 1)
#pragma unroll
        for (int i = 0; i < kT; i++)
#pragma unroll
            for (int j = 0; j < kT; j++) s[i][j] += __shfl_xor_sync(0xffffffffu, s[i][j], off);
#pragma unroll
    for (int i = 0; i < kT; i++) {
        float t[kT];
        float m = -INFINITY;
#pragma unroll
        for (int j = 0; j < kT; j++) {
            const uint32_t w = mw[i * 2 + (j >> 1)];
            const float mk = (j & 1) ? bf_hi(w) : bf_lo(w);
            t[j] = (s[i][j] * kScale + (1.0f - mk) * -1000000000.0f) * kLog2e;
            m = fmaxf(m, t[j]);
        }
        float l = 0.f, o0 = 0.f, o1 = 0.f, o2 = 0.f, o3 = 0.f;
#pragma unroll
        for (int j = 0; j < kT; j++) {
            const float pj = ex2(t[j] - m);
            l += pj;
            o0 = fmaf(pj, bf_lo(vv[j].x), o0);
            o1 = fmaf(pj, bf_hi(vv[j].x), o1);
            o2 = fmaf(pj, bf_lo(vv[j].y), o2);
            o3 = fmaf(pj, bf_hi(vv[j].y), o3);
        }
        r.m[i] = m; r.l[i] = l;
        r.o[i][0] = o0; r.o[i][1] = o1; r.o[i][2] = o2; r.o[i][3] = o3;
    }
}

__device__ __forceinline__ void merge_state(RowState& a, const RowState& b) {
#pragma unroll
    for (int i = 0; i < kT; i++) {
        const float m = fmaxf(a.m[i], b.m[i]);
        const float wa = ex2(a.m[i] - m), wb = ex2(b.m[i] - m);
        a.m[i] = m;
        a.l[i] = a.l[i] * wa + b.l[i] * wb;
#pragma unroll
        for (int e = 0; e < 4; e++) a.o[i][e] = a.o[i][e] * wa + b.o[i][e] * wb;
    }
}

__device__ __forceinline__ void write_out(const Params& p, int head, int lane, const RowState& r) {
#pragma unroll
    for (int i = 0; i < kT; i++) {
        const float inv = __frcp_rn(r.l[i]);
        uint2 v;
        v.x = pack_bf16(r.o[i][0] * inv, r.o[i][1] * inv);
        v.y = pack_bf16(r.o[i][2] * inv, r.o[i][3] * inv);
        *reinterpret_cast<uint2*>(p.out + (size_t)head * (kT * kD) + i * kD + 4 * lane) = v;
    }
}

__global__ void __launch_bounds__(kThreads, 1)
tree_attn_kernel(const __grid_constant__ Params p, const __grid_constant__ CUtensorMap map_k,
                 const __grid_constant__ CUtensorMap map_v) {
    extern __shared__ __align__(1024) uint8_t smem_raw[];
    const uint32_t smem_base = (smem_u32(smem_raw) + 1023u) & ~1023u;
    const uint32_t s_tile = smem_base;
    const uint32_t s_q = s_tile + kSlots * kSlotBytes;
    const uint32_t s_o = s_q + kSlots * kQBytes;
    const uint32_t s_ml = s_o + 3 * 4 * kT * kOStride * 4;
    const uint32_t s_home = s_ml + 3 * 4 * 8 * 4;
    const uint32_t s_meta = s_home + kPartFloats * 4;
    const uint32_t s_cmeta = s_meta + 16;
    const uint32_t s_full = s_cmeta + 16;
    const uint32_t s_empty = s_full + 32;
    const uint32_t s_cfull = s_empty + 32;
    const uint32_t s_cempty = s_cfull + 16;
    const uint32_t s_homebar = s_cempty + 16;

    const int warp = threadIdx.x >> 5;
    const int lane = threadIdx.x & 31;
    uint64_t pol = 0;

    if (warp < 4) {
        const char* pk = reinterpret_cast<const char*>(p.k) + (size_t)blockIdx.x * (kCtx * kD * 2) + threadIdx.x * 128;
        asm volatile("prefetch.global.L2 [%0];" ::"l"(pk) : "memory");
    }
    if (threadIdx.x == 160) {
#pragma unroll
        for (int i = 0; i < kSlots; i++) mbar_init(s_full + i * 8, 1);
        asm volatile("fence.mbarrier_init.release.cluster;" ::: "memory");
        asm volatile("fence.proxy.async.shared::cta;" ::: "memory");
    }
    if (warp == 5) {
        asm volatile("bar.arrive 3, 64;" ::: "memory");
        if (lane == 0) bulk_copy(s_q, p.q + (size_t)blockIdx.x * (kT * kD), kQBytes, s_full);
    }
    if (warp == 4) {
        asm volatile("prefetch.tensormap [%0];" ::"l"(&map_k) : "memory");
        asm volatile("createpolicy.fractional.L2::evict_first.b64 %0, 1.0;" : "=l"(pol));
        asm volatile("bar.sync 3, 64;" ::: "memory");
        if (lane == 0) {
#pragma unroll
            for (int s = 0; s < kSlots; s++) {
                mbar_expect_tx(s_full + s * 8, s == 0 ? kSlotBytes + kQBytes : kSlotBytes);
                tma_tile(s_tile + s * kSlotBytes, (s & 2) ? &map_v : &map_k, blockIdx.x * kCtx + (s & 1) * kTile,
                         s_full + s * 8, pol);
                if (s == 0) sts_u32(s_meta, (KIND_PARK << 11) | blockIdx.x | META_FIRST);
            }
        }
    }
    if (threadIdx.x == 0) {
#pragma unroll
        for (int i = 0; i < kSlots; i++) mbar_init(s_empty + i * 8, 4);
        mbar_init(s_cfull, 4); mbar_init(s_cfull + 8, 4);
        mbar_init(s_cempty, 1); mbar_init(s_cempty + 8, 1);
        mbar_init(s_homebar, 1);
    }
    __syncthreads();

    if (warp == 4) {
        if (lane == 0) {
            const unsigned wrap = (unsigned)(p.npool + gridDim.x - 1);
            uint32_t slot = 0, phase = 0;
            int head = blockIdx.x, t0 = 0, n = kTilesPerHead - kHomeTail, h = kSlots;
            uint32_t tag = KIND_PARK << 11;
            while (true) {
                const bool is_final = (tag >> 11 & 3u) == KIND_FINAL;
                const int fetch_at = is_final ? -1 : (n > kLookAhead ? 2 * (n - kLookAhead) : 0);
                unsigned nxt = 0;
                const int row0 = head * kCtx + t0 * kTile;
                for (; h < 2 * n; h++) {
                    if (h == fetch_at) nxt = atomicInc(&g_queue, wrap);
                    mbar_wait(s_empty + slot * 8, phase);
                    const uint32_t bar = s_full + slot * 8;
                    const int row = row0 + ((h >> 2) * 2 + (h & 1)) * kTile;
                    if (!(h & 2)) {
                        uint32_t meta = tag | (uint32_t)head;
                        if (h == 0) meta |= META_FIRST;
                        if (h == 2 * n - 4) meta |= META_LAST;
                        sts_u32(s_meta + slot * 4, meta);
                        mbar_expect_tx(bar, h == 0 ? kSlotBytes + kQBytes : kSlotBytes);
                        tma_tile(s_tile + slot * kSlotBytes, &map_k, row, bar, pol);
                        if (h == 0) bulk_copy(s_q + slot * kQBytes, p.q + (size_t)head * (kT * kD), kQBytes, bar);
                    } else {
                        mbar_expect_tx(bar, kSlotBytes);
                        tma_tile(s_tile + slot * kSlotBytes, &map_v, row, bar, pol);
                    }
                    if (++slot == kSlots) { slot = 0; phase ^= 1; }
                }
                if (is_final) break;
                h = 0;
                if (nxt < (unsigned)p.nw) {
                    head = gridDim.x + nxt; t0 = 0; n = kTilesPerHead; tag = KIND_WHOLE << 11;
                } else if (nxt < (unsigned)p.npool) {
                    const int r = nxt - p.nw;
                    const int lev = r / p.ns;
                    head = gridDim.x + p.nw + (r - lev * p.ns);
                    t0 = level_start(lev); n = level_len(lev);
                    tag = (KIND_PART << 11) | ((uint32_t)lev << 13);
                } else {
                    head = blockIdx.x; t0 = kTilesPerHead - kHomeTail; n = kHomeTail; tag = KIND_FINAL << 11;
                }
            }
        }
    } else if (warp < 4) {
        const int g = lane >> 2, t = lane & 3;
        uint32_t koff[4], voff[4];
        {
            const uint32_t krow = 16 * warp + (lane & 7) + 8 * ((lane >> 3) & 1);
            const uint32_t kx = (lane >> 4) ^ (lane & 7);
            const uint32_t vrow = 16 * warp + (lane & 7) + 8 * (lane >> 4);
            const uint32_t vx = ((lane >> 3) & 1) ^ (lane & 7);
#pragma unroll
            for (int i = 0; i < 4; i++) {
                koff[i] = s_tile + krow * 128 + (((2 * i) ^ kx) << 4);
                voff[i] = s_tile + vrow * 128 + (((2 * i) ^ vx) << 4);
            }
        }
        float o[8][4], po[8][4];
        float m0 = 0.f, m1 = 0.f, l0 = 0.f, l1 = 0.f, pm0 = 0.f, pm1 = 0.f, pl0 = 0.f, pl1 = 0.f;
        uint32_t qf[8][2];
#pragma unroll
        for (int i = 0; i < 8; i++) {
            qf[i][0] = qf[i][1] = 0;
#pragma unroll
            for (int e = 0; e < 4; e++) { o[i][e] = 0.f; po[i][e] = 0.f; }
        }
        uint32_t slot = 0, phase = 0, cbuf = 0, cphase = 1;
        while (true) {
            mbar_wait(s_full + slot * 8, phase);
            const uint32_t meta = lds_u32(s_meta + slot * 4);
            const uint32_t kind = (meta >> 11) & 3u;
            if (meta & META_FIRST) {
                const uint32_t qa = s_q + slot * kQBytes + (g & 3) * (kD * 2) + t * 4;
#pragma unroll
                for (int ks = 0; ks < 8; ks++) {
                    qf[ks][0] = lds_u32(qa + ks * 32);
                    qf[ks][1] = lds_u32(qa + ks * 32 + 16);
                }
                if (kind == KIND_FINAL) {
                    m0 = pm0; m1 = pm1; l0 = pl0; l1 = pl1;
#pragma unroll
                    for (int i = 0; i < 8; i++)
#pragma unroll
                        for (int e = 0; e < 4; e++) o[i][e] = po[i][e];
                } else {
                    m0 = m1 = -INFINITY; l0 = l1 = 0.f;
#pragma unroll
                    for (int i = 0; i < 8; i++)
#pragma unroll
                        for (int e = 0; e < 4; e++) o[i][e] = 0.f;
                }
            }
            float sc[2][4];
#pragma unroll
            for (int j = 0; j < 2; j++) {
                if (j == 1) mbar_wait(s_full + slot * 8, phase);
                float sa[4] = {0.f, 0.f, 0.f, 0.f}, sb[4] = {0.f, 0.f, 0.f, 0.f};
                const uint32_t kb = slot * kSlotBytes;
#pragma unroll
                for (int ks = 0; ks < 8; ks += 2) {
                    uint32_t a0[4], a1[4];
                    ldsm4(koff[ks & 3] + kb + (ks >> 2) * 8192, a0);
                    ldsm4(koff[(ks + 1) & 3] + kb + (ks >> 2) * 8192, a1);
                    mma_bf16(sa, a0, qf[ks][0], qf[ks][1]);
                    mma_bf16(sb, a1, qf[ks + 1][0], qf[ks + 1][1]);
                }
                __syncwarp();
                if (lane == 0) mbar_arrive(s_empty + slot * 8);
                if (++slot == kSlots) { slot = 0; phase ^= 1; }
#pragma unroll
                for (int e = 0; e < 4; e++) sc[j][e] = sa[e] + sb[e];
            }

            float x0 = fmaxf(fmaxf(sc[0][0], sc[0][2]), fmaxf(sc[1][0], sc[1][2]));
            float x1 = fmaxf(fmaxf(sc[0][1], sc[0][3]), fmaxf(sc[1][1], sc[1][3]));
#pragma unroll
            for (int off = 4; off < 32; off <<= 1) {
                x0 = fmaxf(x0, __shfl_xor_sync(0xffffffffu, x0, off));
                x1 = fmaxf(x1, __shfl_xor_sync(0xffffffffu, x1, off));
            }
            const float n0 = fmaxf(m0, x0 * kScaleLog2e), n1 = fmaxf(m1, x1 * kScaleLog2e);
            const float al0 = ex2(m0 - n0), al1 = ex2(m1 - n1);
            m0 = n0; m1 = n1;
            uint32_t pb[2][2];
            float ps0 = 0.f, ps1 = 0.f;
#pragma unroll
            for (int j = 0; j < 2; j++) {
                const float p0 = ex2(fmaf(sc[j][0], kScaleLog2e, -n0)), p1 = ex2(fmaf(sc[j][1], kScaleLog2e, -n1));
                const float p2 = ex2(fmaf(sc[j][2], kScaleLog2e, -n0)), p3 = ex2(fmaf(sc[j][3], kScaleLog2e, -n1));
                ps0 += p0 + p2;
                ps1 += p1 + p3;
                pb[j][0] = movmatrix_t(pack_bf16(p0, p1));
                pb[j][1] = movmatrix_t(pack_bf16(p2, p3));
            }
            l0 = fmaf(l0, al0, ps0);
            l1 = fmaf(l1, al1, ps1);
#pragma unroll
            for (int i = 0; i < 8; i++) {
                o[i][0] *= al0; o[i][1] *= al1; o[i][2] *= al0; o[i][3] *= al1;
            }
            const bool home_last = (meta & META_LAST) && kind == KIND_FINAL;
            float fsc[4] = {0.f, 0.f, 0.f, 0.f};
            float4 facc = make_float4(0.f, 0.f, 0.f, 0.f);
            if (home_last) {
                float r0 = l0, r1 = l1;
#pragma unroll
                for (int off = 4; off < 32; off <<= 1) {
                    r0 += __shfl_xor_sync(0xffffffffu, r0, off);
                    r1 += __shfl_xor_sync(0xffffffffu, r1, off);
                }
                if (lane < 2) {
                    const uint32_t mb = s_ml + (8 + warp) * 32 + lane * 8;
                    sts_f32(mb, m0); sts_f32(mb + 4, m1);
                    sts_f32(mb + 16, r0); sts_f32(mb + 20, r1);
                }
                mbar_wait(s_cempty + cbuf * 8, cphase);
                if (threadIdx.x == 0) sts_u32(s_cmeta + cbuf * 4, meta);
                __syncwarp();
                if (lane == 0) mbar_arrive(s_cfull + cbuf * 8);
                asm volatile("bar.sync 2, 128;" ::: "memory");
                mbar_wait(s_homebar, 0);
                float mm[5], ll[5];
#pragma unroll
                for (int w = 0; w < 4; w++) {
                    mm[w] = lds_f32(s_ml + (8 + w) * 32 + warp * 4);
                    ll[w] = lds_f32(s_ml + (8 + w) * 32 + 16 + warp * 4);
                }
                mm[4] = lds_f32(s_home + 512 * 4 + warp * 4);
                ll[4] = lds_f32(s_home + 516 * 4 + warp * 4);
                const float4 tv = lds_f32x4(s_home + (warp * kD + 4 * lane) * 4);
                const float m = fmaxf(fmaxf(fmaxf(mm[0], mm[1]), fmaxf(mm[2], mm[3])), mm[4]);
                float l = 0.f;
#pragma unroll
                for (int w = 0; w < 5; w++) {
                    mm[w] = ex2(mm[w] - m);
                    l = fmaf(ll[w], mm[w], l);
                }
                const float inv = __frcp_rn(l);
#pragma unroll
                for (int w = 0; w < 4; w++) fsc[w] = mm[w] * inv;
                const float ts = mm[4] * inv;
                facc = make_float4(tv.x * ts, tv.y * ts, tv.z * ts, tv.w * ts);
            }
#pragma unroll
            for (int j = 0; j < 2; j++) {
                mbar_wait(s_full + slot * 8, phase);
                const uint32_t vb = slot * kSlotBytes;
#pragma unroll
                for (int mt = 0; mt < 8; mt++) {
                    uint32_t a[4];
                    ldsm4_t(voff[mt & 3] + vb + (mt >> 2) * 8192, a);
                    mma_bf16(o[mt], a, pb[j][0], pb[j][1]);
                }
                __syncwarp();
                if (lane == 0) mbar_arrive(s_empty + slot * 8);
                if (++slot == kSlots) { slot = 0; phase ^= 1; }
            }

            if (meta & META_LAST) {
                if (kind == KIND_PARK) {
                    pm0 = m0; pm1 = m1; pl0 = l0; pl1 = l1;
#pragma unroll
                    for (int i = 0; i < 8; i++)
#pragma unroll
                        for (int e = 0; e < 4; e++) po[i][e] = o[i][e];
                    continue;
                }
                if (!home_last) {
#pragma unroll
                    for (int off = 4; off < 32; off <<= 1) {
                        l0 += __shfl_xor_sync(0xffffffffu, l0, off);
                        l1 += __shfl_xor_sync(0xffffffffu, l1, off);
                    }
                    mbar_wait(s_cempty + cbuf * 8, cphase);
                }
                const uint32_t buf = home_last ? 2u : cbuf;
                const uint32_t ob = s_o + (buf * 4 + warp) * (kT * kOStride * 4);
                const int qq = 2 * (t & 1), hi = t >> 1;
                const uint32_t oa = ob + (qq * kOStride + g + 8 * hi) * 4;
#pragma unroll
                for (int mt = 0; mt < 8; mt++) {
                    sts_f32(oa + mt * 64, hi ? o[mt][2] : o[mt][0]);
                    sts_f32(oa + mt * 64 + kOStride * 4, hi ? o[mt][3] : o[mt][1]);
                }
                if (home_last) {
                    asm volatile("bar.sync 2, 128;" ::: "memory");
#pragma unroll
                    for (int w = 0; w < 4; w++) {
                        const float4 v = lds_f32x4(s_o + ((8 + w) * kT * kOStride + warp * kOStride + 4 * lane) * 4);
                        facc.x = fmaf(v.x, fsc[w], facc.x); facc.y = fmaf(v.y, fsc[w], facc.y);
                        facc.z = fmaf(v.z, fsc[w], facc.z); facc.w = fmaf(v.w, fsc[w], facc.w);
                    }
                    uint2 ov;
                    ov.x = pack_bf16(facc.x, facc.y);
                    ov.y = pack_bf16(facc.z, facc.w);
                    *reinterpret_cast<uint2*>(p.out + (size_t)blockIdx.x * (kT * kD) + warp * kD + 4 * lane) = ov;
                    break;
                }
                if (lane < 2) {
                    const uint32_t mb = s_ml + (cbuf * 4 + warp) * 32 + lane * 8;
                    sts_f32(mb, m0); sts_f32(mb + 4, m1);
                    sts_f32(mb + 16, l0); sts_f32(mb + 20, l1);
                }
                if (threadIdx.x == 0) sts_u32(s_cmeta + cbuf * 4, meta);
                __syncwarp();
                if (lane == 0) mbar_arrive(s_cfull + cbuf * 8);
                cbuf ^= 1;
                if (cbuf == 0) cphase ^= 1;
            }
        }
    } else {
        uint32_t cbuf = 0, cphase = 0;
        uint32_t dry = opaque(1u);
        constexpr int nprev = kLevels - 1;
        while (true) {
            uint32_t meta = (KIND_PART << 11) | ((uint32_t)nprev << 13) | blockIdx.x;
            if (!dry) {
                mbar_wait(s_cfull + cbuf * 8, cphase);
                meta = lds_u32(s_cmeta + cbuf * 4);
            }
            const uint32_t kind = (meta >> 11) & 3u;
            if (kind == KIND_FINAL) break;
            const int head = meta & 511u;
            const int piece = (meta >> 13) & 7u;
            RowState r;
            {
                float4 mw[4], lw[4];
#pragma unroll
                for (int w = 0; w < 4; w++) {
                    mw[w] = lds_f32x4(s_ml + (cbuf * 4 + w) * 32);
                    lw[w] = lds_f32x4(s_ml + (cbuf * 4 + w) * 32 + 16);
                }
#pragma unroll
                for (int i = 0; i < kT; i++) {
                    float mm[4], ll[4];
#pragma unroll
                    for (int w = 0; w < 4; w++) {
                        mm[w] = i == 0 ? mw[w].x : i == 1 ? mw[w].y : i == 2 ? mw[w].z : mw[w].w;
                        ll[w] = i == 0 ? lw[w].x : i == 1 ? lw[w].y : i == 2 ? lw[w].z : lw[w].w;
                    }
                    const float m = fmaxf(fmaxf(mm[0], mm[1]), fmaxf(mm[2], mm[3]));
                    float l = 0.f, a0 = 0.f, a1 = 0.f, a2 = 0.f, a3 = 0.f;
#pragma unroll
                    for (int w = 0; w < 4; w++) {
                        const float sc = ex2(mm[w] - m);
                        const float4 v = lds_f32x4(s_o + ((cbuf * 4 + w) * kT * kOStride + i * kOStride + 4 * lane) * 4);
                        l = fmaf(ll[w], sc, l);
                        a0 = fmaf(v.x, sc, a0); a1 = fmaf(v.y, sc, a1); a2 = fmaf(v.z, sc, a2); a3 = fmaf(v.w, sc, a3);
                    }
                    r.m[i] = m; r.l[i] = l;
                    r.o[i][0] = a0; r.o[i][1] = a1; r.o[i][2] = a2; r.o[i][3] = a3;
                }
            }
            if (!dry) {
                __syncwarp();
                if (lane == 0) mbar_arrive(s_cempty + cbuf * 8);
                cbuf ^= 1;
                if (cbuf == 0) cphase ^= 1;
            }

            if (dry || kind == KIND_WHOLE || piece == 0) {
                RowState tr;
                tree_part(p, head, lane, tr);
                if (dry) {
#pragma unroll
                    for (int i = 0; i < kT; i++) {
#pragma unroll
                        for (int e = 0; e < 4; e++) sts_f32(s_home + (i * kD + 4 * lane + e) * 4, tr.o[i][e]);
                        if (lane == 0) { sts_f32(s_home + (512 + i) * 4, tr.m[i]); sts_f32(s_home + (516 + i) * 4, tr.l[i]); }
                    }
                    __syncwarp();
                    if (lane == 0) mbar_arrive(s_homebar);
                }
                merge_state(r, tr);
            }
            if (dry) { dry = 0; continue; }
            if (kind == KIND_PART) {
                float* part = g_part + (size_t)head * (nprev * kPartFloats);
                if (piece < nprev) {
                    float* dst = part + piece * kPartFloats;
#pragma unroll
                    for (int i = 0; i < kT; i++) st_part(dst + i * kD + 4 * lane, r.o[i][0], r.o[i][1], r.o[i][2], r.o[i][3]);
                    if (lane == 0) {
                        st_part(dst + 512, r.m[0], r.m[1], r.m[2], r.m[3]);
                        st_part(dst + 516, r.l[0], r.l[1], r.l[2], r.l[3]);
                    }
                    continue;
                }
                uint4 pm[nprev], pl[nprev], pv[nprev][kT];
                for (int tries = 0;; tries++) {
#pragma unroll
                    for (int k = 0; k < nprev; k++) {
                        const float* src = part + k * kPartFloats;
                        pm[k] = ld_part(src + 512);
                        pl[k] = ld_part(src + 516);
#pragma unroll
                        for (int i = 0; i < kT; i++) pv[k][i] = ld_part(src + i * kD + 4 * lane);
                    }
                    bool ok = true;
#pragma unroll
                    for (int k = 0; k < nprev; k++) {
                        ok &= all_set(pm[k]) && all_set(pl[k]);
#pragma unroll
                        for (int i = 0; i < kT; i++) ok &= all_set(pv[k][i]);
                    }
                    if (__all_sync(0xffffffffu, ok)) break;
                    if (tries > 2000000) __trap();
                }
#pragma unroll
                for (int k = 0; k < nprev; k++) {
                    float* src = part + k * kPartFloats;
#pragma unroll
                    for (int i = 0; i < kT; i++) clear_part(src + i * kD + 4 * lane);
                    if (lane < 2) clear_part(src + 512 + 4 * lane);
                }
#pragma unroll
                for (int i = 0; i < kT; i++) {
                    float mm[nprev], ll[nprev];
#pragma unroll
                    for (int k = 0; k < nprev; k++) {
                        mm[k] = comp(pm[k], i);
                        ll[k] = comp(pl[k], i);
                    }
                    float m = r.m[i];
#pragma unroll
                    for (int k = 0; k < nprev; k++) m = fmaxf(m, mm[k]);
                    float l = 0.f, a0 = 0.f, a1 = 0.f, a2 = 0.f, a3 = 0.f;
#pragma unroll
                    for (int k = 0; k < nprev; k++) {
                        const float sc = ex2(mm[k] - m);
                        l = fmaf(ll[k], sc, l);
                        a0 = fmaf(comp(pv[k][i], 0), sc, a0); a1 = fmaf(comp(pv[k][i], 1), sc, a1);
                        a2 = fmaf(comp(pv[k][i], 2), sc, a2); a3 = fmaf(comp(pv[k][i], 3), sc, a3);
                    }
                    const float sc = ex2(r.m[i] - m);
                    r.m[i] = m;
                    r.l[i] = fmaf(r.l[i], sc, l);
                    r.o[i][0] = fmaf(r.o[i][0], sc, a0); r.o[i][1] = fmaf(r.o[i][1], sc, a1);
                    r.o[i][2] = fmaf(r.o[i][2], sc, a2); r.o[i][3] = fmaf(r.o[i][3], sc, a3);
                }
            }
            write_out(p, head, lane, r);
        }
    }
}

typedef CUresult (*EncodeTiledFn)(CUtensorMap*, CUtensorMapDataType, cuuint32_t, void*, const cuuint64_t*,
                                  const cuuint64_t*, const cuuint32_t*, const cuuint32_t*, CUtensorMapInterleave,
                                  CUtensorMapSwizzle, CUtensorMapL2promotion, CUtensorMapFloatOOBfill);

void make_map(EncodeTiledFn enc, CUtensorMap* m, const void* ptr) {
    cuuint64_t dims[3] = {64, (cuuint64_t)kNumHeads * kCtx, 2};
    cuuint64_t strides[2] = {kD * 2, 128};
    cuuint32_t box[3] = {64, (cuuint32_t)kTile, 2};
    cuuint32_t estr[3] = {1, 1, 1};
    enc(m, CU_TENSOR_MAP_DATA_TYPE_BFLOAT16, 3, const_cast<void*>(ptr), dims, strides, box, estr,
        CU_TENSOR_MAP_INTERLEAVE_NONE, CU_TENSOR_MAP_SWIZZLE_128B, CU_TENSOR_MAP_L2_PROMOTION_L2_256B,
        CU_TENSOR_MAP_FLOAT_OOB_FILL_NONE);
}

constexpr int kSmemBytes = 1024 + kSlots * (kSlotBytes + kQBytes) + 3 * 4 * kT * kOStride * 4 + 3 * 4 * 8 * 4 +
                           kPartFloats * 4 + 16 + 16 + 32 + 32 + 16 + 16 + 16;

}

extern "C" void kernel_launch(void* const* d_in, const int* in_sizes, int n_in, void* d_out, int out_size) {
    (void)in_sizes; (void)n_in; (void)out_size;
    static EncodeTiledFn enc = nullptr;
    static int num_sms = 0;
    if (!enc) {
        void* fn = nullptr;
        cudaDriverEntryPointQueryResult qr;
        cudaGetDriverEntryPoint("cuTensorMapEncodeTiled", &fn, cudaEnableDefault, &qr);
        enc = (EncodeTiledFn)fn;
        int dev = 0;
        cudaGetDevice(&dev);
        cudaDeviceGetAttribute(&num_sms, cudaDevAttrMultiProcessorCount, dev);
        cudaFuncSetAttribute(tree_attn_kernel, cudaFuncAttributeMaxDynamicSharedMemorySize, kSmemBytes);
    }
    CUtensorMap mk, mv;
    make_map(enc, &mk, d_in[1]);
    make_map(enc, &mv, d_in[2]);

    const int grid = num_sms < kNumHeads ? num_sms : kNumHeads;

    Params p;
    p.q = (const __nv_bfloat16*)d_in[0];
    p.k = (const __nv_bfloat16*)d_in[1];
    p.kt = (const __nv_bfloat16*)d_in[3];
    p.vt = (const __nv_bfloat16*)d_in[4];
    p.mask = (const __nv_bfloat16*)d_in[5];
    p.out = (__nv_bfloat16*)d_out;
    p.ns = kSplitHeads < kNumHeads - grid ? kSplitHeads : kNumHeads - grid;
    p.nw = kNumHeads - grid - p.ns;
    p.npool = p.nw + p.ns * kLevels;
    tree_attn_kernel<<<grid, kThreads, kSmemBytes>>>(p, mk, mv);
}
```

```cpp
#include <cuda_runtime.h>
#include <cuda_bf16.h>
#include <cuda.h>
#include <stdint.h>

namespace {

constexpr int kBatch = 16, kHeads = 32, kT = 4, kCtx = 2048, kD = 128;
constexpr int kNumHeads = kBatch * kHeads;
constexpr int kTile = 64;
constexpr int kTilesPerHead = kCtx / kTile;
constexpr int kSlotBytes = kTile * kD * 2;
constexpr int kQBytes = kT * kD * 2;
constexpr int kSlots = 4;
constexpr int kHomeTail = 4;
constexpr int kFinal = 2 * kHomeTail;
constexpr int kSplitHeads = 132;
constexpr int kLevels = 5;
constexpr int kLookAhead = 1;
constexpr int kOStride = 136;
constexpr int kPartFloats = 520;
constexpr int kThreads = 192;

constexpr uint32_t kFinalDepth0 = 0x22333233u, kFinalDepth1 = 0x22333333u;
constexpr uint32_t kFinalDepth2 = 0x22333444u, kFinalDepth3 = 0x22444444u;

constexpr uint32_t KIND_WHOLE = 0, KIND_PARK = 1, KIND_FINAL = 2, KIND_PART = 3;
constexpr uint32_t META_FIRST = 1u << 9, META_LAST = 1u << 10;

struct Params {
    const __nv_bfloat16* q;
    const __nv_bfloat16* k;
    const __nv_bfloat16* kt;
    const __nv_bfloat16* vt;
    const __nv_bfloat16* mask;
    __nv_bfloat16* out;
    int nw;
    int ns;
    int npool;
};

__host__ __device__ constexpr int level_len(int lev) { return lev < 3 ? 16 >> lev : 2; }
__host__ __device__ constexpr int level_start(int lev) { return lev < 4 ? 32 - (32 >> lev) : 30; }
static_assert(level_start(kLevels - 1) + level_len(kLevels - 1) == kTilesPerHead, "pieces must cover a head");
static_assert(level_len(kLevels - 1) % 2 == 0 && (kTilesPerHead - kHomeTail) % 2 == 0, "units are whole tile pairs");
static_assert(kSlots == 4 && kHomeTail == 4, "slot indexing assumes K K V V rings and a four-tile tail");
constexpr bool depths_ok(uint32_t row) {
    for (int j = 0; j < kFinal; j++) {
        const int d = (row >> (4 * j)) & 15;
        if (d < 1 || d > kSlots) return false;
    }
    return true;
}
static_assert(depths_ok(kFinalDepth0) && depths_ok(kFinalDepth1) && depths_ok(kFinalDepth2) && depths_ok(kFinalDepth3),
              "tail pacing starts from the ring");

__device__ unsigned int g_queue;
__device__ float g_part[kNumHeads * (kLevels - 1) * kPartFloats];

__device__ __forceinline__ uint32_t smem_u32(const void* p) { return (uint32_t)__cvta_generic_to_shared(p); }
__device__ __forceinline__ void mbar_init(uint32_t bar, uint32_t cnt) {
    asm volatile("mbarrier.init.shared::cta.b64 [%0], %1;" ::"r"(bar), "r"(cnt) : "memory");
}
__device__ __forceinline__ void mbar_arrive(uint32_t bar) {
    asm volatile("mbarrier.arrive.shared::cta.b64 _, [%0];" ::"r"(bar) : "memory");
}
__device__ __forceinline__ void mbar_expect_tx(uint32_t bar, uint32_t bytes) {
    asm volatile("mbarrier.arrive.expect_tx.shared::cta.b64 _, [%0], %1;" ::"r"(bar), "r"(bytes) : "memory");
}
__device__ __forceinline__ bool mbar_try(uint32_t bar, uint32_t parity) {
    uint32_t ok;
    asm volatile(
        "{\n.reg .pred p;\n"
        "mbarrier.try_wait.parity.shared::cta.b64 p, [%1], %2;\n"
        "selp.u32 %0, 1, 0, p;\n}"
        : "=r"(ok) : "r"(bar), "r"(parity) : "memory");
    return ok != 0;
}
__device__ __forceinline__ void mbar_wait(uint32_t bar, uint32_t parity) {
    if (mbar_try(bar, parity)) return;
    const long long t0 = clock64();
    while (!mbar_try(bar, parity)) {
        if (clock64() - t0 > 4000000000LL) __trap();
    }
}
__device__ __forceinline__ void tma_tile(uint32_t dst, const CUtensorMap* map, int row, uint32_t bar, uint64_t pol) {
    asm volatile("cp.async.bulk.tensor.3d.shared::cluster.global.mbarrier::complete_tx::bytes.L2::cache_hint"
                 " [%0], [%1, {%3, %4, %3}], [%2], %5;"
                 ::"r"(dst), "l"(map), "r"(bar), "r"(0), "r"(row), "l"(pol) : "memory");
}
__device__ __forceinline__ void bulk_copy(uint32_t dst, const void* src, uint32_t bytes, uint32_t bar) {
    asm volatile("cp.async.bulk.shared::cluster.global.mbarrier::complete_tx::bytes [%0], [%1], %2, [%3];"
                 ::"r"(dst), "l"(src), "r"(bytes), "r"(bar) : "memory");
}
__device__ __forceinline__ void ldsm4(uint32_t addr, uint32_t (&r)[4]) {
    asm volatile("ldmatrix.sync.aligned.m8n8.x4.shared.b16 {%0,%1,%2,%3}, [%4];"
                 : "=r"(r[0]), "=r"(r[1]), "=r"(r[2]), "=r"(r[3]) : "r"(addr) : "memory");
}
__device__ __forceinline__ void ldsm4_t(uint32_t addr, uint32_t (&r)[4]) {
    asm volatile("ldmatrix.sync.aligned.m8n8.x4.trans.shared.b16 {%0,%1,%2,%3}, [%4];"
                 : "=r"(r[0]), "=r"(r[1]), "=r"(r[2]), "=r"(r[3]) : "r"(addr) : "memory");
}
__device__ __forceinline__ void mma_bf16(float (&c)[4], const uint32_t (&a)[4], uint32_t b0, uint32_t b1) {
    asm volatile("mma.sync.aligned.m16n8k16.row.col.f32.bf16.bf16.f32 {%0,%1,%2,%3}, {%4,%5,%6,%7}, {%8,%9}, {%0,%1,%2,%3};"
                 : "+f"(c[0]), "+f"(c[1]), "+f"(c[2]), "+f"(c[3])
                 : "r"(a[0]), "r"(a[1]), "r"(a[2]), "r"(a[3]), "r"(b0), "r"(b1));
}
__device__ __forceinline__ uint32_t pack_bf16(float lo, float hi) {
    uint32_t r;
    asm("cvt.rn.bf16x2.f32 %0, %1, %2;" : "=r"(r) : "f"(hi), "f"(lo));
    return r;
}
__device__ __forceinline__ uint32_t movmatrix_t(uint32_t a) {
    uint32_t d;
    asm volatile("movmatrix.sync.aligned.m8n8.trans.b16 %0, %1;" : "=r"(d) : "r"(a));
    return d;
}
__device__ __forceinline__ float ex2(float x) {
    float y;
    asm("ex2.approx.ftz.f32 %0, %1;" : "=f"(y) : "f"(x));
    return y;
}
__device__ __forceinline__ float bf_lo(uint32_t v) { return __uint_as_float(v << 16); }
__device__ __forceinline__ float bf_hi(uint32_t v) { return __uint_as_float(v & 0xffff0000u); }
__device__ __forceinline__ float lds_f32(uint32_t a) {
    float v;
    asm volatile("ld.shared.f32 %0, [%1];" : "=f"(v) : "r"(a) : "memory");
    return v;
}
__device__ __forceinline__ uint32_t lds_u32(uint32_t a) {
    uint32_t v;
    asm volatile("ld.shared.u32 %0, [%1];" : "=r"(v) : "r"(a) : "memory");
    return v;
}
__device__ __forceinline__ uint2 lds_u32x2(uint32_t a) {
    uint2 v;
    asm volatile("ld.shared.v2.u32 {%0,%1}, [%2];" : "=r"(v.x), "=r"(v.y) : "r"(a) : "memory");
    return v;
}
__device__ __forceinline__ void sts_u32x2(uint32_t a, uint32_t x, uint32_t y) {
    asm volatile("st.shared.v2.u32 [%0], {%1,%2};" ::"r"(a), "r"(x), "r"(y) : "memory");
}
__device__ __forceinline__ float4 lds_f32x4(uint32_t a) {
    float4 v;
    asm volatile("ld.shared.v4.f32 {%0,%1,%2,%3}, [%4];" : "=f"(v.x), "=f"(v.y), "=f"(v.z), "=f"(v.w) : "r"(a) : "memory");
    return v;
}
__device__ __forceinline__ void sts_f32(uint32_t a, float v) { asm volatile("st.shared.f32 [%0], %1;" ::"r"(a), "f"(v) : "memory"); }
__device__ __forceinline__ void sts_u32(uint32_t a, uint32_t v) { asm volatile("st.shared.u32 [%0], %1;" ::"r"(a), "r"(v) : "memory"); }

__device__ __forceinline__ uint32_t enc_word(float x) { return max(__float_as_uint(x), 1u); }
__device__ __forceinline__ void st_part(float* p, float a, float b, float c, float d) {
    asm volatile("st.relaxed.gpu.global.v4.b32 [%0], {%1,%2,%3,%4};"
                 ::"l"(p), "r"(enc_word(a)), "r"(enc_word(b)), "r"(enc_word(c)), "r"(enc_word(d)) : "memory");
}
__device__ __forceinline__ void clear_part(float* p) {
    asm volatile("st.relaxed.gpu.global.v4.b32 [%0], {%1,%1,%1,%1};" ::"l"(p), "r"(0u) : "memory");
}
__device__ __forceinline__ uint4 ld_part(const float* p) {
    uint4 v;
    asm volatile("ld.relaxed.gpu.global.v4.b32 {%0,%1,%2,%3}, [%4];"
                 : "=r"(v.x), "=r"(v.y), "=r"(v.z), "=r"(v.w) : "l"(p) : "memory");
    return v;
}
__device__ __forceinline__ bool all_set(const uint4& v) { return v.x != 0 && v.y != 0 && v.z != 0 && v.w != 0; }
__device__ __forceinline__ float comp(const uint4& v, int i) {
    return __uint_as_float(i == 0 ? v.x : i == 1 ? v.y : i == 2 ? v.z : v.w);
}

constexpr float kLog2e = 1.4426950408889634f;
constexpr float kScale = 0.08838834764831845f;
constexpr float kScaleLog2e = kScale * kLog2e;

struct RowState {
    float o[kT][4];
    float m[kT];
    float l[kT];
};

__device__ __forceinline__ void tree_part(const Params& p, int head, int lane, RowState& r) {
    const size_t base = (size_t)head * (kT * kD) + 4 * lane;
    uint2 qv[kT], kv[kT], vv[kT];
#pragma unroll
    for (int i = 0; i < kT; i++) {
        qv[i] = __ldg(reinterpret_cast<const uint2*>(p.q + base + i * kD));
        kv[i] = __ldg(reinterpret_cast<const uint2*>(p.kt + base + i * kD));
        vv[i] = __ldg(reinterpret_cast<const uint2*>(p.vt + base + i * kD));
    }
    const uint4* mp = reinterpret_cast<const uint4*>(p.mask + (size_t)(head / kHeads) * (kT * kT));
    const uint4 mk0 = __ldg(mp), mk1 = __ldg(mp + 1);
    const uint32_t mw[8] = {mk0.x, mk0.y, mk0.z, mk0.w, mk1.x, mk1.y, mk1.z, mk1.w};
    float s[kT][kT];
#pragma unroll
    for (int i = 0; i < kT; i++)
#pragma unroll
        for (int j = 0; j < kT; j++) {
            float a = bf_lo(qv[i].x) * bf_lo(kv[j].x);
            a = fmaf(bf_hi(qv[i].x), bf_hi(kv[j].x), a);
            a = fmaf(bf_lo(qv[i].y), bf_lo(kv[j].y), a);
            a = fmaf(bf_hi(qv[i].y), bf_hi(kv[j].y), a);
            s[i][j] = a;
        }
#pragma unroll
    for (int off = 16; off > 0; off >>= 1)
#pragma unroll
        for (int i = 0; i < kT; i++)
#pragma unroll
            for (int j = 0; j < kT; j++) s[i][j] += __shfl_xor_sync(0xffffffffu, s[i][j], off);
#pragma unroll
    for (int i = 0; i < kT; i++) {
        float t[kT];
        float m = -INFINITY;
#pragma unroll
        for (int j = 0; j < kT; j++) {
            const uint32_t w = mw[i * 2 + (j >> 1)];
            const float mk = (j & 1) ? bf_hi(w) : bf_lo(w);
            t[j] = (s[i][j] * kScale + (1.0f - mk) * -1000000000.0f) * kLog2e;
            m = fmaxf(m, t[j]);
        }
        float l = 0.f, o0 = 0.f, o1 = 0.f, o2 = 0.f, o3 = 0.f;
#pragma unroll
        for (int j = 0; j < kT; j++) {
            const float pj = ex2(t[j] - m);
            l += pj;
            o0 = fmaf(pj, bf_lo(vv[j].x), o0);
            o1 = fmaf(pj, bf_hi(vv[j].x), o1);
            o2 = fmaf(pj, bf_lo(vv[j].y), o2);
            o3 = fmaf(pj, bf_hi(vv[j].y), o3);
        }
        r.m[i] = m; r.l[i] = l;
        r.o[i][0] = o0; r.o[i][1] = o1; r.o[i][2] = o2; r.o[i][3] = o3;
    }
}

__device__ __forceinline__ void merge_state(RowState& a, const RowState& b) {
#pragma unroll
    for (int i = 0; i < kT; i++) {
        const float m = fmaxf(a.m[i], b.m[i]);
        const float wa = ex2(a.m[i] - m), wb = ex2(b.m[i] - m);
        a.m[i] = m;
        a.l[i] = a.l[i] * wa + b.l[i] * wb;
#pragma unroll
        for (int e = 0; e < 4; e++) a.o[i][e] = a.o[i][e] * wa + b.o[i][e] * wb;
    }
}

__device__ __forceinline__ void write_out(const Params& p, int head, int lane, const RowState& r) {
#pragma unroll
    for (int i = 0; i < kT; i++) {
        const float inv = __frcp_rn(r.l[i]);
        uint2 v;
        v.x = pack_bf16(r.o[i][0] * inv, r.o[i][1] * inv);
        v.y = pack_bf16(r.o[i][2] * inv, r.o[i][3] * inv);
        *reinterpret_cast<uint2*>(p.out + (size_t)head * (kT * kD) + i * kD + 4 * lane) = v;
    }
}

__global__ void __launch_bounds__(kThreads, 1)
tree_attn_kernel(const __grid_constant__ Params p, const __grid_constant__ CUtensorMap map_k,
                 const __grid_constant__ CUtensorMap map_v) {
    extern __shared__ __align__(1024) uint8_t smem_raw[];
    const uint32_t smem_base = (smem_u32(smem_raw) + 1023u) & ~1023u;
    const uint32_t s_tile = smem_base;
    const uint32_t s_q = s_tile + (kSlots + kFinal) * kSlotBytes;
    const uint32_t s_o = s_q + (kSlots + 1) * kQBytes;
    const uint32_t s_ml = s_o + 2 * 4 * kT * kOStride * 4;
    const uint32_t s_home = s_ml + 3 * 4 * 8 * 4;
    const uint32_t s_p = s_home + (kT * kOStride + 8) * 4;
    const uint32_t s_meta = s_p + 4 * kHomeTail * 32 * 8;
    const uint32_t s_cmeta = s_meta + 16;
    const uint32_t s_full = s_cmeta + 16;
    const uint32_t s_empty = s_full + 32;
    const uint32_t s_cfull = s_empty + 32;
    const uint32_t s_cempty = s_cfull + 16;
    const uint32_t s_homebar = s_cempty + 16;
    const uint32_t s_fbar = s_homebar + 16;

    const int warp = threadIdx.x >> 5;
    const int lane = threadIdx.x & 31;
    uint64_t pol = 0;

    if (warp < 4) {
        const char* pk = reinterpret_cast<const char*>(p.k) + (size_t)blockIdx.x * (kCtx * kD * 2) + threadIdx.x * 128;
        asm volatile("prefetch.global.L2 [%0];" ::"l"(pk) : "memory");
    }
    if (threadIdx.x == 160) {
#pragma unroll
        for (int i = 0; i < kSlots; i++) mbar_init(s_full + i * 8, 1);
        asm volatile("fence.mbarrier_init.release.cluster;" ::: "memory");
        asm volatile("fence.proxy.async.shared::cta;" ::: "memory");
    }
    if (warp == 5) {
        asm volatile("bar.arrive 3, 64;" ::: "memory");
        if (lane == 0) {
            bulk_copy(s_q, p.q + (size_t)blockIdx.x * (kT * kD), kQBytes, s_full);
            bulk_copy(s_q + kSlots * kQBytes, p.q + (size_t)blockIdx.x * (kT * kD), kQBytes, s_full);
        }
    }
    if (warp == 4) {
        asm volatile("prefetch.tensormap [%0];" ::"l"(&map_k) : "memory");
        asm volatile("createpolicy.fractional.L2::evict_first.b64 %0, 1.0;" : "=l"(pol));
        asm volatile("bar.sync 3, 64;" ::: "memory");
        if (lane == 0) {
#pragma unroll
            for (int s = 0; s < kSlots; s++) {
                mbar_expect_tx(s_full + s * 8, s == 0 ? kSlotBytes + 2 * kQBytes : kSlotBytes);
                tma_tile(s_tile + s * kSlotBytes, (s & 2) ? &map_v : &map_k, blockIdx.x * kCtx + (s & 1) * kTile,
                         s_full + s * 8, pol);
                if (s == 0) sts_u32(s_meta, (KIND_PARK << 11) | blockIdx.x | META_FIRST);
            }
        }
    }
    if (threadIdx.x == 0) {
#pragma unroll
        for (int i = 0; i < kSlots; i++) mbar_init(s_empty + i * 8, 4);
        mbar_init(s_cfull, 4); mbar_init(s_cfull + 8, 4);
        mbar_init(s_cempty, 1); mbar_init(s_cempty + 8, 1);
        mbar_init(s_homebar, 1);
#pragma unroll
        for (int i = 0; i < kFinal; i++) mbar_init(s_fbar + i * 8, 1);
        asm volatile("fence.mbarrier_init.release.cluster;" ::: "memory");
        asm volatile("fence.proxy.async.shared::cta;" ::: "memory");
    }
    __syncthreads();

    if (warp == 4) {
        if (lane == 0) {
            const unsigned wrap = (unsigned)(p.npool + gridDim.x - 1);
            uint32_t slot = 0, phase = 0;
            int head = blockIdx.x, t0 = 0, n = kTilesPerHead - kHomeTail, h = kSlots;
            uint32_t tag = KIND_PARK << 11;
            unsigned nxt = 0;
            while (true) {
                const int fetch_at = 2 * (n - kLookAhead);
                const int row0 = head * kCtx + t0 * kTile;
                for (; h < 2 * n; h++) {
                    if (h == fetch_at) nxt = atomicInc(&g_queue, wrap);
                    mbar_wait(s_empty + slot * 8, phase);
                    const uint32_t bar = s_full + slot * 8;
                    const int row = row0 + ((h >> 2) * 2 + (h & 1)) * kTile;
                    if (!(h & 2)) {
                        uint32_t meta = tag | (uint32_t)head;
                        if (h == 0) meta |= META_FIRST;
                        if (h == 2 * n - 4) meta |= META_LAST;
                        sts_u32(s_meta + slot * 4, meta);
                        mbar_expect_tx(bar, h == 0 ? kSlotBytes + kQBytes : kSlotBytes);
                        tma_tile(s_tile + slot * kSlotBytes, &map_k, row, bar, pol);
                        if (h == 0) bulk_copy(s_q + slot * kQBytes, p.q + (size_t)head * (kT * kD), kQBytes, bar);
                    } else {
                        mbar_expect_tx(bar, kSlotBytes);
                        tma_tile(s_tile + slot * kSlotBytes, &map_v, row, bar, pol);
                    }
                    if (++slot == kSlots) { slot = 0; phase ^= 1; }
                }
                h = 0;
                if (nxt < (unsigned)p.nw) {
                    head = gridDim.x + nxt; t0 = 0; n = kTilesPerHead; tag = KIND_WHOLE << 11;
                } else if (nxt < (unsigned)p.npool) {
                    const int r = nxt - p.nw;
                    const int lev = r / p.ns;
                    head = gridDim.x + p.nw + (r - lev * p.ns);
                    t0 = level_start(lev); n = level_len(lev);
                    tag = (KIND_PART << 11) | ((uint32_t)lev << 13);
                } else {
                    break;
                }
            }
            const int row0 = blockIdx.x * kCtx + (kTilesPerHead - kHomeTail) * kTile;
            const unsigned r4 = 4u * (nxt - (unsigned)p.npool);
            const uint32_t depths = r4 < gridDim.x ? kFinalDepth0 : r4 < 2 * gridDim.x ? kFinalDepth1
                                  : r4 < 3 * gridDim.x ? kFinalDepth2 : kFinalDepth3;
            int waited = 0;
#pragma unroll 1
            for (int j = 0; j < kFinal; j++) {
                const int c = j + kSlots - (int)((depths >> (4 * j)) & 15u);
                while (waited <= c && waited < kSlots) {
                    mbar_wait(s_empty + slot * 8, phase);
                    if (waited == 0) {
                        sts_u32(s_meta + slot * 4, KIND_FINAL << 11);
                        mbar_arrive(s_full + slot * 8);
                    }
                    if (++slot == kSlots) { slot = 0; phase ^= 1; }
                    waited++;
                }
                if (c >= kSlots) mbar_wait(s_fbar + (c - kSlots) * 8, 0);
                const uint32_t bar = s_fbar + j * 8;
                mbar_expect_tx(bar, kSlotBytes);
                tma_tile(s_tile + (kSlots + j) * kSlotBytes, j < kHomeTail ? &map_k : &map_v,
                         row0 + (j & (kHomeTail - 1)) * kTile, bar, pol);
            }
        }
    } else if (warp < 4) {
        const int g = lane >> 2, t = lane & 3;
        uint32_t koff[4], voff[4];
        {
            const uint32_t krow = 16 * warp + (lane & 7) + 8 * ((lane >> 3) & 1);
            const uint32_t kx = (lane >> 4) ^ (lane & 7);
            const uint32_t vrow = 16 * warp + (lane & 7) + 8 * (lane >> 4);
            const uint32_t vx = ((lane >> 3) & 1) ^ (lane & 7);
#pragma unroll
            for (int i = 0; i < 4; i++) {
                koff[i] = s_tile + krow * 128 + (((2 * i) ^ kx) << 4);
                voff[i] = s_tile + vrow * 128 + (((2 * i) ^ vx) << 4);
            }
        }
        float o[8][4];
        float m0 = 0.f, m1 = 0.f, l0 = 0.f, l1 = 0.f;
        uint32_t qf[8][2];
#pragma unroll
        for (int i = 0; i < 8; i++) {
            qf[i][0] = qf[i][1] = 0;
#pragma unroll
            for (int e = 0; e < 4; e++) o[i][e] = 0.f;
        }
        uint32_t slot = 0, phase = 0, cbuf = 0, cphase = 1;
        while (true) {
            mbar_wait(s_full + slot * 8, phase);
            const uint32_t meta = lds_u32(s_meta + slot * 4);
            if (((meta >> 11) & 3u) == KIND_FINAL) {
                mbar_wait(s_cempty + cbuf * 8, cphase);
                if (threadIdx.x == 0) sts_u32(s_cmeta + cbuf * 4, meta);
                __syncwarp();
                if (lane == 0) mbar_arrive(s_cfull + cbuf * 8);
                break;
            }
            if (meta & META_FIRST) {
                const uint32_t qa = s_q + slot * kQBytes + (g & 3) * (kD * 2) + t * 4;
#pragma unroll
                for (int ks = 0; ks < 8; ks++) {
                    qf[ks][0] = lds_u32(qa + ks * 32);
                    qf[ks][1] = lds_u32(qa + ks * 32 + 16);
                }
                m0 = m1 = -INFINITY; l0 = l1 = 0.f;
#pragma unroll
                for (int i = 0; i < 8; i++)
#pragma unroll
                    for (int e = 0; e < 4; e++) o[i][e] = 0.f;
            }
            float sc[2][4];
#pragma unroll
            for (int j = 0; j < 2; j++) {
                if (j == 1) mbar_wait(s_full + slot * 8, phase);
                float sa[4] = {0.f, 0.f, 0.f, 0.f}, sb[4] = {0.f, 0.f, 0.f, 0.f};
                const uint32_t kb = slot * kSlotBytes;
#pragma unroll
                for (int ks = 0; ks < 8; ks += 2) {
                    uint32_t a0[4], a1[4];
                    ldsm4(koff[ks & 3] + kb + (ks >> 2) * 8192, a0);
                    ldsm4(koff[(ks + 1) & 3] + kb + (ks >> 2) * 8192, a1);
                    mma_bf16(sa, a0, qf[ks][0], qf[ks][1]);
                    mma_bf16(sb, a1, qf[ks + 1][0], qf[ks + 1][1]);
                }
                __syncwarp();
                if (lane == 0) mbar_arrive(s_empty + slot * 8);
                if (++slot == kSlots) { slot = 0; phase ^= 1; }
#pragma unroll
                for (int e = 0; e < 4; e++) sc[j][e] = sa[e] + sb[e];
            }

            float x0 = fmaxf(fmaxf(sc[0][0], sc[0][2]), fmaxf(sc[1][0], sc[1][2]));
            float x1 = fmaxf(fmaxf(sc[0][1], sc[0][3]), fmaxf(sc[1][1], sc[1][3]));
#pragma unroll
            for (int off = 4; off < 32; off <<= 1) {
                x0 = fmaxf(x0, __shfl_xor_sync(0xffffffffu, x0, off));
                x1 = fmaxf(x1, __shfl_xor_sync(0xffffffffu, x1, off));
            }
            const float n0 = fmaxf(m0, x0 * kScaleLog2e), n1 = fmaxf(m1, x1 * kScaleLog2e);
            const float al0 = ex2(m0 - n0), al1 = ex2(m1 - n1);
            m0 = n0; m1 = n1;
            uint32_t pb[2][2];
            float ps0 = 0.f, ps1 = 0.f;
#pragma unroll
            for (int j = 0; j < 2; j++) {
                const float p0 = ex2(fmaf(sc[j][0], kScaleLog2e, -n0)), p1 = ex2(fmaf(sc[j][1], kScaleLog2e, -n1));
                const float p2 = ex2(fmaf(sc[j][2], kScaleLog2e, -n0)), p3 = ex2(fmaf(sc[j][3], kScaleLog2e, -n1));
                ps0 += p0 + p2;
                ps1 += p1 + p3;
                pb[j][0] = movmatrix_t(pack_bf16(p0, p1));
                pb[j][1] = movmatrix_t(pack_bf16(p2, p3));
            }
            l0 = fmaf(l0, al0, ps0);
            l1 = fmaf(l1, al1, ps1);
#pragma unroll
            for (int i = 0; i < 8; i++) {
                o[i][0] *= al0; o[i][1] *= al1; o[i][2] *= al0; o[i][3] *= al1;
            }
#pragma unroll
            for (int j = 0; j < 2; j++) {
                mbar_wait(s_full + slot * 8, phase);
                const uint32_t vb = slot * kSlotBytes;
#pragma unroll
                for (int mt = 0; mt < 8; mt++) {
                    uint32_t a[4];
                    ldsm4_t(voff[mt & 3] + vb + (mt >> 2) * 8192, a);
                    mma_bf16(o[mt], a, pb[j][0], pb[j][1]);
                }
                __syncwarp();
                if (lane == 0) mbar_arrive(s_empty + slot * 8);
                if (++slot == kSlots) { slot = 0; phase ^= 1; }
            }

            if (meta & META_LAST) {
#pragma unroll
                for (int off = 4; off < 32; off <<= 1) {
                    l0 += __shfl_xor_sync(0xffffffffu, l0, off);
                    l1 += __shfl_xor_sync(0xffffffffu, l1, off);
                }
                mbar_wait(s_cempty + cbuf * 8, cphase);
                const uint32_t ob = s_o + (cbuf * 4 + warp) * (kT * kOStride * 4);
                const int qq = 2 * (t & 1), hi = t >> 1;
                const uint32_t oa = ob + (qq * kOStride + g + 8 * hi) * 4;
#pragma unroll
                for (int mt = 0; mt < 8; mt++) {
                    sts_f32(oa + mt * 64, hi ? o[mt][2] : o[mt][0]);
                    sts_f32(oa + mt * 64 + kOStride * 4, hi ? o[mt][3] : o[mt][1]);
                }
                if (lane < 2) {
                    const uint32_t mb = s_ml + (cbuf * 4 + warp) * 32 + lane * 8;
                    sts_f32(mb, m0); sts_f32(mb + 4, m1);
                    sts_f32(mb + 16, l0); sts_f32(mb + 20, l1);
                }
                if (threadIdx.x == 0) sts_u32(s_cmeta + cbuf * 4, meta);
                __syncwarp();
                if (lane == 0) mbar_arrive(s_cfull + cbuf * 8);
                cbuf ^= 1;
                if (cbuf == 0) cphase ^= 1;
            }
        }

        const int q0 = 2 * (t & 1);
        mbar_wait(s_homebar, 0);
        float pre[2][4];
#pragma unroll
        for (int mt = 0; mt < 2; mt++)
#pragma unroll
            for (int e = 0; e < 4; e++)
                pre[mt][e] = lds_f32(s_home + ((q0 + (e & 1)) * kOStride + 32 * warp + 16 * mt + 8 * (e >> 1) + g) * 4);
        const float hm0 = lds_f32(s_home + (kT * kOStride + q0) * 4), hm1 = lds_f32(s_home + (kT * kOStride + q0 + 1) * 4);
        const float hl0 = lds_f32(s_home + (kT * kOStride + 4 + q0) * 4), hl1 = lds_f32(s_home + (kT * kOStride + 5 + q0) * 4);
        float sc[kHomeTail][4];
#pragma unroll
        for (int j = 0; j < kHomeTail; j++) {
            mbar_wait(s_fbar + j * 8, 0);
            if (j == 0) {
                const uint32_t qa = s_q + kSlots * kQBytes + (g & 3) * (kD * 2) + t * 4;
#pragma unroll
                for (int ks = 0; ks < 8; ks++) {
                    qf[ks][0] = lds_u32(qa + ks * 32);
                    qf[ks][1] = lds_u32(qa + ks * 32 + 16);
                }
            }
            float sa[4] = {0.f, 0.f, 0.f, 0.f}, sb[4] = {0.f, 0.f, 0.f, 0.f};
            const uint32_t kb = (kSlots + j) * kSlotBytes;
#pragma unroll
            for (int ks = 0; ks < 8; ks += 2) {
                uint32_t a0[4], a1[4];
                ldsm4(koff[ks & 3] + kb + (ks >> 2) * 8192, a0);
                ldsm4(koff[(ks + 1) & 3] + kb + (ks >> 2) * 8192, a1);
                mma_bf16(sa, a0, qf[ks][0], qf[ks][1]);
                mma_bf16(sb, a1, qf[ks + 1][0], qf[ks + 1][1]);
            }
#pragma unroll
            for (int e = 0; e < 4; e++) sc[j][e] = sa[e] + sb[e];
        }
        float x0 = -INFINITY, x1 = -INFINITY;
#pragma unroll
        for (int j = 0; j < kHomeTail; j++) {
            x0 = fmaxf(x0, fmaxf(sc[j][0], sc[j][2]));
            x1 = fmaxf(x1, fmaxf(sc[j][1], sc[j][3]));
        }
#pragma unroll
        for (int off = 4; off < 32; off <<= 1) {
            x0 = fmaxf(x0, __shfl_xor_sync(0xffffffffu, x0, off));
            x1 = fmaxf(x1, __shfl_xor_sync(0xffffffffu, x1, off));
        }
        m0 = x0 * kScaleLog2e; m1 = x1 * kScaleLog2e;
        l0 = l1 = 0.f;
#pragma unroll
        for (int j = 0; j < kHomeTail; j++) {
            const float p0 = ex2(fmaf(sc[j][0], kScaleLog2e, -m0)), p1 = ex2(fmaf(sc[j][1], kScaleLog2e, -m1));
            const float p2 = ex2(fmaf(sc[j][2], kScaleLog2e, -m0)), p3 = ex2(fmaf(sc[j][3], kScaleLog2e, -m1));
            l0 += p0 + p2;
            l1 += p1 + p3;
            sts_u32x2(s_p + ((warp * kHomeTail + j) * 32 + lane) * 8, movmatrix_t(pack_bf16(p0, p1)), movmatrix_t(pack_bf16(p2, p3)));
        }
#pragma unroll
        for (int off = 4; off < 32; off <<= 1) {
            l0 += __shfl_xor_sync(0xffffffffu, l0, off);
            l1 += __shfl_xor_sync(0xffffffffu, l1, off);
        }
        if (lane < 2) {
            const uint32_t mb = s_ml + (8 + warp) * 32 + lane * 8;
            sts_f32(mb, m0); sts_f32(mb + 4, m1);
            sts_f32(mb + 16, l0); sts_f32(mb + 20, l1);
        }
        asm volatile("bar.sync 2, 128;" ::: "memory");
        float fs[4][2];
        {
            float ll[4][2];
            float ma = hm0, mb = hm1;
#pragma unroll
            for (int w = 0; w < 4; w++) {
                const uint2 a = lds_u32x2(s_ml + (8 + w) * 32 + q0 * 4), b = lds_u32x2(s_ml + (8 + w) * 32 + 16 + q0 * 4);
                fs[w][0] = __uint_as_float(a.x); fs[w][1] = __uint_as_float(a.y);
                ll[w][0] = __uint_as_float(b.x); ll[w][1] = __uint_as_float(b.y);
                ma = fmaxf(ma, fs[w][0]); mb = fmaxf(mb, fs[w][1]);
            }
            const float ga = ex2(hm0 - ma), gb = ex2(hm1 - mb);
            float la = hl0 * ga, lb = hl1 * gb;
#pragma unroll
            for (int w = 0; w < 4; w++) {
                fs[w][0] = ex2(fs[w][0] - ma); fs[w][1] = ex2(fs[w][1] - mb);
                la = fmaf(ll[w][0], fs[w][0], la); lb = fmaf(ll[w][1], fs[w][1], lb);
            }
            const float ia = __frcp_rn(la), ib = __frcp_rn(lb);
#pragma unroll
            for (int w = 0; w < 4; w++) { fs[w][0] *= ia; fs[w][1] *= ib; }
#pragma unroll
            for (int mt = 0; mt < 2; mt++) {
                pre[mt][0] *= ga * ia; pre[mt][1] *= gb * ib; pre[mt][2] *= ga * ia; pre[mt][3] *= gb * ib;
            }
        }
#pragma unroll
        for (int i = 0; i < 8; i++)
#pragma unroll
            for (int e = 0; e < 4; e++) o[i][e] = 0.f;
        uint32_t va[2];
#pragma unroll
        for (int mt = 0; mt < 2; mt++)
            va[mt] = s_tile + (kSlots + kHomeTail) * kSlotBytes + (warp >> 1) * 8192 + ((lane & 7) + 8 * (lane >> 4)) * 128 +
                     (((2 * ((2 * warp + mt) & 3)) ^ (((lane >> 3) & 1) ^ (lane & 7))) << 4);
        __nv_bfloat16* const dst = p.out + (size_t)blockIdx.x * (kT * kD) + (g & 3) * kD + 32 * warp + 2 * t;
#pragma unroll 1
        for (int j = 0; j < kHomeTail; j++) {
            uint2 pf[4];
#pragma unroll
            for (int w = 0; w < 4; w++) pf[w] = lds_u32x2(s_p + ((w * kHomeTail + j) * 32 + lane) * 8);
            mbar_wait(s_fbar + (kHomeTail + j) * 8, 0);
#pragma unroll
            for (int w = 0; w < 4; w++)
#pragma unroll
                for (int mt = 0; mt < 2; mt++) {
                    uint32_t a[4];
                    ldsm4_t(va[mt] + j * kSlotBytes + w * 2048, a);
                    mma_bf16(o[2 * w + mt], a, pf[w].x, pf[w].y);
                }
#pragma unroll
            for (int mt = 0; mt < 2; mt++)
#pragma unroll
                for (int hh = 0; hh < 2; hh++) {
                    float r0 = pre[mt][2 * hh], r1 = pre[mt][2 * hh + 1];
#pragma unroll
                    for (int w = 0; w < 4; w++) {
                        r0 = fmaf(o[2 * w + mt][2 * hh], fs[w][0], r0);
                        r1 = fmaf(o[2 * w + mt][2 * hh + 1], fs[w][1], r1);
                    }
                    const uint32_t u = movmatrix_t(pack_bf16(r0, r1));
                    if (j == kHomeTail - 1 && g < 4) *reinterpret_cast<uint32_t*>(dst + 16 * mt + 8 * hh) = u;
                }
        }
    } else {
        uint32_t cbuf = 0, cphase = 0;
        constexpr int nprev = kLevels - 1;
        while (true) {
            mbar_wait(s_cfull + cbuf * 8, cphase);
            const uint32_t meta = lds_u32(s_cmeta + cbuf * 4);
            const uint32_t kind = (meta >> 11) & 3u;
            if (kind == KIND_FINAL) break;
            const int head = meta & 511u;
            const int piece = (meta >> 13) & 7u;
            RowState r;
            {
                float4 mw[4], lw[4];
#pragma unroll
                for (int w = 0; w < 4; w++) {
                    mw[w] = lds_f32x4(s_ml + (cbuf * 4 + w) * 32);
                    lw[w] = lds_f32x4(s_ml + (cbuf * 4 + w) * 32 + 16);
                }
#pragma unroll
                for (int i = 0; i < kT; i++) {
                    float mm[4], ll[4];
#pragma unroll
                    for (int w = 0; w < 4; w++) {
                        mm[w] = i == 0 ? mw[w].x : i == 1 ? mw[w].y : i == 2 ? mw[w].z : mw[w].w;
                        ll[w] = i == 0 ? lw[w].x : i == 1 ? lw[w].y : i == 2 ? lw[w].z : lw[w].w;
                    }
                    const float m = fmaxf(fmaxf(mm[0], mm[1]), fmaxf(mm[2], mm[3]));
                    float l = 0.f, a0 = 0.f, a1 = 0.f, a2 = 0.f, a3 = 0.f;
#pragma unroll
                    for (int w = 0; w < 4; w++) {
                        const float sc = ex2(mm[w] - m);
                        const float4 v = lds_f32x4(s_o + ((cbuf * 4 + w) * kT * kOStride + i * kOStride + 4 * lane) * 4);
                        l = fmaf(ll[w], sc, l);
                        a0 = fmaf(v.x, sc, a0); a1 = fmaf(v.y, sc, a1); a2 = fmaf(v.z, sc, a2); a3 = fmaf(v.w, sc, a3);
                    }
                    r.m[i] = m; r.l[i] = l;
                    r.o[i][0] = a0; r.o[i][1] = a1; r.o[i][2] = a2; r.o[i][3] = a3;
                }
            }
            __syncwarp();
            if (lane == 0) mbar_arrive(s_cempty + cbuf * 8);
            cbuf ^= 1;
            if (cbuf == 0) cphase ^= 1;

            if (kind != KIND_PART || piece == 0) {
                RowState tr;
                tree_part(p, head, lane, tr);
                merge_state(r, tr);
            }
            if (kind == KIND_PARK) {
#pragma unroll
                for (int i = 0; i < kT; i++) {
#pragma unroll
                    for (int e = 0; e < 4; e++) sts_f32(s_home + (i * kOStride + 4 * lane + e) * 4, r.o[i][e]);
                    if (lane == 0) {
                        sts_f32(s_home + (kT * kOStride + i) * 4, r.m[i]);
                        sts_f32(s_home + (kT * kOStride + 4 + i) * 4, r.l[i]);
                    }
                }
                __syncwarp();
                if (lane == 0) mbar_arrive(s_homebar);
                continue;
            }
            if (kind == KIND_PART) {
                float* part = g_part + (size_t)head * (nprev * kPartFloats);
                if (piece < nprev) {
                    float* dst = part + piece * kPartFloats;
#pragma unroll
                    for (int i = 0; i < kT; i++) st_part(dst + i * kD + 4 * lane, r.o[i][0], r.o[i][1], r.o[i][2], r.o[i][3]);
                    if (lane == 0) {
                        st_part(dst + 512, r.m[0], r.m[1], r.m[2], r.m[3]);
                        st_part(dst + 516, r.l[0], r.l[1], r.l[2], r.l[3]);
                    }
                    continue;
                }
                uint4 pm[nprev], pl[nprev], pv[nprev][kT];
                for (int tries = 0;; tries++) {
#pragma unroll
                    for (int k = 0; k < nprev; k++) {
                        const float* src = part + k * kPartFloats;
                        pm[k] = ld_part(src + 512);
                        pl[k] = ld_part(src + 516);
#pragma unroll
                        for (int i = 0; i < kT; i++) pv[k][i] = ld_part(src + i * kD + 4 * lane);
                    }
                    bool ok = true;
#pragma unroll
                    for (int k = 0; k < nprev; k++) {
                        ok &= all_set(pm[k]) && all_set(pl[k]);
#pragma unroll
                        for (int i = 0; i < kT; i++) ok &= all_set(pv[k][i]);
                    }
                    if (__all_sync(0xffffffffu, ok)) break;
                    if (tries > 2000000) __trap();
                }
#pragma unroll
                for (int k = 0; k < nprev; k++) {
                    float* src = part + k * kPartFloats;
#pragma unroll
                    for (int i = 0; i < kT; i++) clear_part(src + i * kD + 4 * lane);
                    if (lane < 2) clear_part(src + 512 + 4 * lane);
                }
#pragma unroll
                for (int i = 0; i < kT; i++) {
                    float mm[nprev], ll[nprev];
#pragma unroll
                    for (int k = 0; k < nprev; k++) {
                        mm[k] = comp(pm[k], i);
                        ll[k] = comp(pl[k], i);
                    }
                    float m = r.m[i];
#pragma unroll
                    for (int k = 0; k < nprev; k++) m = fmaxf(m, mm[k]);
                    float l = 0.f, a0 = 0.f, a1 = 0.f, a2 = 0.f, a3 = 0.f;
#pragma unroll
                    for (int k = 0; k < nprev; k++) {
                        const float sc = ex2(mm[k] - m);
                        l = fmaf(ll[k], sc, l);
                        a0 = fmaf(comp(pv[k][i], 0), sc, a0); a1 = fmaf(comp(pv[k][i], 1), sc, a1);
                        a2 = fmaf(comp(pv[k][i], 2), sc, a2); a3 = fmaf(comp(pv[k][i], 3), sc, a3);
                    }
                    const float sc = ex2(r.m[i] - m);
                    r.m[i] = m;
                    r.l[i] = fmaf(r.l[i], sc, l);
                    r.o[i][0] = fmaf(r.o[i][0], sc, a0); r.o[i][1] = fmaf(r.o[i][1], sc, a1);
                    r.o[i][2] = fmaf(r.o[i][2], sc, a2); r.o[i][3] = fmaf(r.o[i][3], sc, a3);
                }
            }
            write_out(p, head, lane, r);
        }
    }
}

typedef CUresult (*EncodeTiledFn)(CUtensorMap*, CUtensorMapDataType, cuuint32_t, void*, const cuuint64_t*,
                                  const cuuint64_t*, const cuuint32_t*, const cuuint32_t*, CUtensorMapInterleave,
                                  CUtensorMapSwizzle, CUtensorMapL2promotion, CUtensorMapFloatOOBfill);

void make_map(EncodeTiledFn enc, CUtensorMap* m, const void* ptr) {
    cuuint64_t dims[3] = {64, (cuuint64_t)kNumHeads * kCtx, 2};
    cuuint64_t strides[2] = {kD * 2, 128};
    cuuint32_t box[3] = {64, (cuuint32_t)kTile, 2};
    cuuint32_t estr[3] = {1, 1, 1};
    enc(m, CU_TENSOR_MAP_DATA_TYPE_BFLOAT16, 3, const_cast<void*>(ptr), dims, strides, box, estr,
        CU_TENSOR_MAP_INTERLEAVE_NONE, CU_TENSOR_MAP_SWIZZLE_128B, CU_TENSOR_MAP_L2_PROMOTION_L2_256B,
        CU_TENSOR_MAP_FLOAT_OOB_FILL_NONE);
}

constexpr int kSmemBytes = 1024 + (kSlots + kFinal) * kSlotBytes + (kSlots + 1) * kQBytes + 2 * 4 * kT * kOStride * 4 +
                           3 * 4 * 8 * 4 + (kT * kOStride + 8) * 4 + 4 * kHomeTail * 32 * 8 +
                           16 + 16 + 32 + 32 + 16 + 16 + 16 + kFinal * 8;

}

extern "C" void kernel_launch(void* const* d_in, const int* in_sizes, int n_in, void* d_out, int out_size) {
    (void)in_sizes; (void)n_in; (void)out_size;
    static EncodeTiledFn enc = nullptr;
    static int num_sms = 0;
    if (!enc) {
        void* fn = nullptr;
        cudaDriverEntryPointQueryResult qr;
        cudaGetDriverEntryPoint("cuTensorMapEncodeTiled", &fn, cudaEnableDefault, &qr);
        enc = (EncodeTiledFn)fn;
        int dev = 0;
        cudaGetDevice(&dev);
        cudaDeviceGetAttribute(&num_sms, cudaDevAttrMultiProcessorCount, dev);
        cudaFuncSetAttribute(tree_attn_kernel, cudaFuncAttributeMaxDynamicSharedMemorySize, kSmemBytes);
    }
    CUtensorMap mk, mv;
    make_map(enc, &mk, d_in[1]);
    make_map(enc, &mv, d_in[2]);

    const int grid = num_sms < kNumHeads ? num_sms : kNumHeads;

    Params p;
    p.q = (const __nv_bfloat16*)d_in[0];
    p.k = (const __nv_bfloat16*)d_in[1];
    p.kt = (const __nv_bfloat16*)d_in[3];
    p.vt = (const __nv_bfloat16*)d_in[4];
    p.mask = (const __nv_bfloat16*)d_in[5];
    p.out = (__nv_bfloat16*)d_out;
    p.ns = kSplitHeads < kNumHeads - grid ? kSplitHeads : kNumHeads - grid;
    p.nw = kNumHeads - grid - p.ns;
    p.npool = p.nw + p.ns * kLevels;
    tree_attn_kernel<<<grid, kThreads, kSmemBytes>>>(p, mk, mv);
}
```
